```python
import torch

def _softmax(x, axis=-1):
    return torch.softmax(x, dim=axis)
def _gelu(x):
    return torch.nn.functional.gelu(x, approximate="tanh")
def _silu(x):
    return torch.nn.functional.silu(x)
def _sigmoid(x):
    return torch.sigmoid(x)
def _layernorm(x, axis=-1, eps=1e-5):
    m = x.mean(dim=axis, keepdim=True)
    v = x.var(dim=axis, keepdim=True, unbiased=False)
    return (x - m) / torch.sqrt(v + eps)
def _scatter_add(tgt, idx, src, axis=0):
    return tgt.clone().index_add_(axis, idx, src)
def _segment_sum(src, seg, n):
    out = torch.zeros((n,) + src.shape[1:], dtype=src.dtype)
    return out.index_add_(0, seg, src)
def _pad(x, pw):
    flat = tuple(v for pair in reversed(pw) for v in pair)
    return torch.nn.functional.pad(x, flat)

kernel_name = 'interleave_layers__sliding_block_cached__glu_gated_swiglu__decode'

def setup_inputs():

    _w = (lambda a: (lambda t: t.to(torch.bfloat16) if t.is_floating_point() else t)(torch.as_tensor(a)))
    def _A_setup():
        B, Sq, D = 1, 1, 512
        Hq, Hkv, Sk, Dh = 32, 32, 4096, 128
        assert Hq % Hkv == 0, (Hq, Hkv)
        return {
            "x": _w((lambda *s: torch.randn(*s, dtype=torch.bfloat16) * 0.05)(B, Sq, D)),
            "k_cache": _w((lambda *s: torch.randn(*s, dtype=torch.bfloat16) * 0.8)(B, Hkv, Sk, Dh)),
            "v_cache": _w((lambda *s: torch.randn(*s, dtype=torch.bfloat16) * 0.8)(B, Hkv, Sk, Dh)),
            "wq": _w((lambda *s: torch.randn(*s, dtype=torch.bfloat16) * 0.8)(D, Hq * Dh) * (D ** -0.5)),
            "wo": _w((lambda *s: torch.randn(*s, dtype=torch.bfloat16) * 0.8)(Hq * Dh, D) * ((Hq * Dh) ** -0.5)),
        }
    _A_in = _A_setup()

    def _B_setup():
        B, S, D, F = 1, 1, 512, 1376
        return {
            "x": _w((lambda *s: torch.randn(*s, dtype=torch.bfloat16) * 0.05)(B, S, D)),
            "w1": _w((lambda *s: torch.randn(*s, dtype=torch.bfloat16) * 0.2)(D, F) * (2.0 / D) ** 0.5),
            "w3": _w((lambda *s: torch.randn(*s, dtype=torch.bfloat16) * 0.2)(D, F) * (2.0 / D) ** 0.5),
            "w2": _w((lambda *s: torch.randn(*s, dtype=torch.bfloat16) * 0.2)(F, D) * (2.0 / F) ** 0.5),
        }
    _B_in = _B_setup()

    return {
        "A_x": _A_in["x"],
        "A_k_cache": _A_in["k_cache"],
        "A_v_cache": _A_in["v_cache"],
        "A_wq": _A_in["wq"],
        "A_wo": _A_in["wo"],
        "B_x": _B_in["x"],
        "B_w1": _B_in["w1"],
        "B_w3": _B_in["w3"],
        "B_w2": _B_in["w2"],
    }

def reference(A_x, A_k_cache, A_v_cache, A_wq, A_wo, B_x, B_w1, B_w3, B_w2):
    def _A_ref(x, k_cache, v_cache, wq, wo):
        B, Sq, D = x.shape
        Hq, Dh = 32, 128
        Hkv, Sk = k_cache.shape[1], k_cache.shape[2]
        W = min(4096, max(256, Sk // 4))
        rep = Hq // Hkv
        q = (lambda x, *d: x.permute(*d))((x @ wq).reshape(B, Sq, Hq, Dh), 0, 2, 1, 3)
        k = (lambda x, n, axis: torch.repeat_interleave(x, n, dim=axis))(k_cache[:, :, Sk - W:, :], rep, axis=1)
        v = (lambda x, n, axis: torch.repeat_interleave(x, n, dim=axis))(v_cache[:, :, Sk - W:, :], rep, axis=1)
        scores = torch.einsum("bhqd,bhkd->bhqk", q, k) * (Dh ** -0.5)
        p = _softmax(scores, axis=-1)
        o = torch.einsum("bhqk,bhkd->bhqd", p, v)
        return (lambda x, *d: x.permute(*d))(o, 0, 2, 1, 3).reshape(B, Sq, Hq * Dh) @ wo

    def _B_ref(x, w1, w3, w2):
        gate = torch.einsum("bsd,df->bsf", x, w1)
        up = torch.einsum("bsd,df->bsf", x, w3)
        h = _silu(gate) * up
        out = torch.einsum("bsf,fd->bsd", h, w2)
        return out

    x = A_x
    x = x + _A_ref(_layernorm(x, axis=-1), A_k_cache, A_v_cache, A_wq, A_wo)
    x = x + _B_ref(_layernorm(x, axis=-1), B_w1, B_w3, B_w2)
    x = x + _A_ref(_layernorm(x, axis=-1), A_k_cache, A_v_cache, A_wq, A_wo)
    x = x + _B_ref(_layernorm(x, axis=-1), B_w1, B_w3, B_w2)
    return x
```

```cpp
#include <cuda_runtime.h>
#include <cuda_bf16.h>
#include <cuda.h>
#include <stdint.h>

namespace {

constexpr int NCTA = 128;
constexpr int NTHR = 256;
constexpr int NFFN = 86;
constexpr int SPIN_LIMIT = 1 << 22;

constexpr uint32_t OFF_WQ = 0;
constexpr uint32_t OFF_K = 65536;
constexpr uint32_t OFF_V = 131072;
constexpr uint32_t OFF_W1 = OFF_V;
constexpr uint32_t OFF_W3 = OFF_V + 16384;
constexpr uint32_t OFF_W2 = OFF_V + 32768;
constexpr uint32_t OFF_XS = 196608;
constexpr uint32_t OFF_PS = OFF_XS + 1024;
constexpr uint32_t OFF_SX = OFF_PS + 1024;
constexpr uint32_t OFF_FP = OFF_SX + 2048;
constexpr uint32_t OFF_QS = OFF_FP + 1024;
constexpr uint32_t OFF_OS = OFF_QS + 128;
constexpr uint32_t OFF_M = OFF_OS + 128;
constexpr uint32_t OFF_L = OFF_M + 32;
constexpr uint32_t OFF_BAR = OFF_L + 32;
constexpr uint32_t BAR_WQ = OFF_BAR;
constexpr uint32_t BAR_K = BAR_WQ + 8;
constexpr uint32_t BAR_V = BAR_K + 64;
constexpr uint32_t BAR_WO = BAR_V + 32;
constexpr uint32_t BAR_W13 = BAR_WO + 64;
constexpr uint32_t BAR_W2 = BAR_W13 + 8;
constexpr uint32_t BAR_SX = BAR_W2 + 8;
constexpr uint32_t NBAR = 31;
constexpr uint32_t SMEM_BYTES = OFF_BAR + NBAR * 8 + 8;

struct Maps { CUtensorMap wq, k, v, wo, w1, w3, w2; };

__device__ __align__(128) unsigned char g_acc_raw[65536];
__device__ __align__(128) float2 g_ml[2][NCTA][16];
#define STAMP(k) do {} while (0)

__device__ __forceinline__ void mbar_init(uint32_t a, int c) {
    asm volatile("mbarrier.init.shared::cta.b64 [%0], %1;" ::"r"(a), "r"(c) : "memory");
}
__device__ __forceinline__ void mbar_expect(uint32_t a, uint32_t bytes) {
    asm volatile("mbarrier.arrive.expect_tx.shared::cta.b64 _, [%0], %1;" ::"r"(a), "r"(bytes) : "memory");
}
__device__ __forceinline__ void mbar_wait(uint32_t a, uint32_t parity) {
    uint32_t ok;
    int n = 0;
    do {
        asm volatile("{\n.reg .pred p;\nmbarrier.try_wait.parity.shared::cta.b64 p, [%1], %2;\nselp.u32 %0, 1, 0, p;\n}"
                     : "=r"(ok) : "r"(a), "r"(parity) : "memory");
    } while (!ok && ++n < SPIN_LIMIT);
}
__device__ __forceinline__ void mbar_wait_cluster(uint32_t a, uint32_t parity) {
    uint32_t ok;
    int n = 0;
    do {
        asm volatile("{\n.reg .pred p;\nmbarrier.try_wait.parity.acquire.cluster.shared::cta.b64 p, [%1], %2;\nselp.u32 %0, 1, 0, p;\n}"
                     : "=r"(ok) : "r"(a), "r"(parity) : "memory");
    } while (!ok && ++n < SPIN_LIMIT);
}
__device__ __forceinline__ void tma2d(uint32_t dst, const CUtensorMap* m, int c0, int c1, uint32_t bar) {
    asm volatile("cp.async.bulk.tensor.2d.shared::cluster.global.mbarrier::complete_tx::bytes [%0], [%1, {%3, %4}], [%2];"
                 ::"r"(dst), "l"(m), "r"(bar), "r"(c0), "r"(c1) : "memory");
}
__device__ __forceinline__ void ldsm4(uint32_t* r, uint32_t a) {
    asm volatile("ldmatrix.sync.aligned.m8n8.x4.shared.b16 {%0,%1,%2,%3}, [%4];"
                 : "=r"(r[0]), "=r"(r[1]), "=r"(r[2]), "=r"(r[3]) : "r"(a) : "memory");
}
__device__ __forceinline__ void ldsm4t(uint32_t* r, uint32_t a) {
    asm volatile("ldmatrix.sync.aligned.m8n8.x4.trans.shared.b16 {%0,%1,%2,%3}, [%4];"
                 : "=r"(r[0]), "=r"(r[1]), "=r"(r[2]), "=r"(r[3]) : "r"(a) : "memory");
}
__device__ __forceinline__ void mma(float* c, const uint32_t* a, uint32_t b0, uint32_t b1) {
    asm("mma.sync.aligned.m16n8k16.row.col.f32.bf16.bf16.f32 {%0,%1,%2,%3},{%4,%5,%6,%7},{%8,%9},{%0,%1,%2,%3};"
        : "+f"(c[0]), "+f"(c[1]), "+f"(c[2]), "+f"(c[3])
        : "r"(a[0]), "r"(a[1]), "r"(a[2]), "r"(a[3]), "r"(b0), "r"(b1));
}
__device__ __forceinline__ uint4 lds128(uint32_t a) {
    uint4 v;
    asm volatile("ld.shared.v4.u32 {%0,%1,%2,%3}, [%4];" : "=r"(v.x), "=r"(v.y), "=r"(v.z), "=r"(v.w) : "r"(a) : "memory");
    return v;
}
__device__ __forceinline__ float4 lds128f(uint32_t a) {
    float4 v;
    asm volatile("ld.shared.v4.f32 {%0,%1,%2,%3}, [%4];" : "=f"(v.x), "=f"(v.y), "=f"(v.z), "=f"(v.w) : "r"(a) : "memory");
    return v;
}
__device__ __forceinline__ float2 lds64f(uint32_t a) {
    float2 v;
    asm volatile("ld.shared.v2.f32 {%0,%1}, [%2];" : "=f"(v.x), "=f"(v.y) : "r"(a) : "memory");
    return v;
}
__device__ __forceinline__ float lds32f(uint32_t a) {
    float v;
    asm volatile("ld.shared.f32 %0, [%1];" : "=f"(v) : "r"(a) : "memory");
    return v;
}
__device__ __forceinline__ void sts16(uint32_t a, uint32_t v) {
    asm volatile("st.shared.u16 [%0], %1;" ::"r"(a), "h"((unsigned short)v) : "memory");
}
__device__ __forceinline__ void sts32f(uint32_t a, float v) {
    asm volatile("st.shared.f32 [%0], %1;" ::"r"(a), "f"(v) : "memory");
}
__device__ __forceinline__ void sts128f(uint32_t a, float x, float y, float z, float w) {
    asm volatile("st.shared.v4.f32 [%0], {%1,%2,%3,%4};" ::"r"(a), "f"(x), "f"(y), "f"(z), "f"(w) : "memory");
}
__device__ __forceinline__ void cta_sync() { asm volatile("bar.sync 0;" ::: "memory"); }
__device__ __forceinline__ float ex2(float x) {
    float y;
    asm("ex2.approx.ftz.f32 %0, %1;" : "=f"(y) : "f"(x));
    return y;
}
__device__ __forceinline__ float rcp(float x) {
    float y;
    asm("rcp.approx.ftz.f32 %0, %1;" : "=f"(y) : "f"(x));
    return y;
}
__device__ __forceinline__ uint32_t pack_bf16(float lo, float hi) {
    uint32_t r;
    asm("cvt.rn.bf16x2.f32 %0, %1, %2;" : "=r"(r) : "f"(hi), "f"(lo));
    return r;
}
__device__ __forceinline__ float bf16r(float x) { return __uint_as_float(pack_bf16(0.f, x) & 0xffff0000u); }
__device__ __forceinline__ float4 ld_relaxed4(const void* p) {
    float4 v;
    asm volatile("ld.relaxed.gpu.global.v4.f32 {%0,%1,%2,%3}, [%4];" : "=f"(v.x), "=f"(v.y), "=f"(v.z), "=f"(v.w) : "l"(p) : "memory");
    return v;
}
__device__ __forceinline__ float2 ld_relaxed2(const void* p) {
    float2 v;
    asm volatile("ld.relaxed.gpu.global.v2.f32 {%0,%1}, [%2];" : "=f"(v.x), "=f"(v.y) : "l"(p) : "memory");
    return v;
}
__device__ __forceinline__ void st_relaxed2(void* p, float x, float y) {
    asm volatile("st.relaxed.gpu.global.v2.f32 [%0], {%1,%2};" ::"l"(p), "f"(x), "f"(y) : "memory");
}
__device__ __forceinline__ void st_relaxed4(void* p, float x, float y, float z, float w) {
    asm volatile("st.relaxed.gpu.global.v4.f32 [%0], {%1,%2,%3,%4};" ::"l"(p), "f"(x), "f"(y), "f"(z), "f"(w) : "memory");
}
__device__ __forceinline__ void red4(void* p, float x, float y, float z, float w) {
    asm volatile("red.relaxed.gpu.global.add.v4.f32 [%0], {%1,%2,%3,%4};" ::"l"(p), "f"(x), "f"(y), "f"(z), "f"(w) : "memory");
}
__device__ __forceinline__ float4 atom4(void* p, float x, float y, float z, float w) {
    float4 v;
    asm volatile("atom.relaxed.gpu.global.add.v4.f32 {%0,%1,%2,%3}, [%4], {%5,%6,%7,%8};"
                 : "=f"(v.x), "=f"(v.y), "=f"(v.z), "=f"(v.w) : "l"(p), "f"(x), "f"(y), "f"(z), "f"(w) : "memory");
    return v;
}
__device__ __forceinline__ constexpr uint32_t eoff(int e) { return (uint32_t)((e & 1) * 128 + (e >> 1) * 512); }

constexpr uint32_t ONES = 0x3F803F80u;

__device__ __forceinline__ void poll_update(const unsigned char* p, float target, bool own, float* xo) {
    float4 v = make_float4(0.f, 0.f, 0.f, target);
    int n = 0;
    bool ok = !own;
    do {
        if (!ok) {
            v = ld_relaxed4(p);
            ok = (v.w == target);
        }
    } while (!__all_sync(0xffffffffu, ok) && ++n < SPIN_LIMIT);
    xo[0] = bf16r(xo[0] + bf16r(v.x));
    xo[1] = bf16r(xo[1] + bf16r(v.y));
    xo[2] = bf16r(xo[2] + bf16r(v.z));
}

__device__ __forceinline__ void ln_stats(uint32_t sb, int lane, float shift, float& mean, float& rstd) {
    uint4 u0 = lds128(sb + OFF_XS + lane * 16);
    uint4 u1 = lds128(sb + OFF_XS + 512 + lane * 16);
    uint32_t u[8] = {u0.x, u0.y, u0.z, u0.w, u1.x, u1.y, u1.z, u1.w};
    float s0 = 0.f, s1 = 0.f, q0 = 0.f, q1 = 0.f;
#pragma unroll
    for (int i = 0; i < 8; i++) {
        float a = __uint_as_float(u[i] << 16) - shift;
        float c = __uint_as_float(u[i] & 0xffff0000u) - shift;
        s0 += a; s1 += c;
        q0 = fmaf(a, a, q0); q1 = fmaf(c, c, q1);
    }
    float s = s0 + s1, q = q0 + q1;
#pragma unroll
    for (int o = 16; o > 0; o >>= 1) {
        s += __shfl_xor_sync(0xffffffffu, s, o);
        q += __shfl_xor_sync(0xffffffffu, q, o);
    }
    float ms = s * (1.f / 512.f);
    float var = fmaxf(fmaf(-ms, ms, q * (1.f / 512.f)), 0.f);
    mean = ms + shift;
    rstd = rsqrtf(var + 1e-5f);
}

__global__ void __cluster_dims__(2, 1, 1) __launch_bounds__(NTHR, 1)
fused_kernel(const __grid_constant__ Maps mp, const __nv_bfloat16* __restrict__ x_in, __nv_bfloat16* __restrict__ out) {
    extern __shared__ __align__(1024) unsigned char smem[];
    const uint32_t sb = (uint32_t)__cvta_generic_to_shared(smem);
    const int tid = threadIdx.x, w = tid >> 5, lane = tid & 31, g = lane >> 2, t = lane & 3;
    const int b = blockIdx.x, r = b & 1, pr = (b >> 1) & 1, h = b >> 2;
    const bool ffn = b < NFFN;

    if (tid == 0) {
        for (uint32_t i = 0; i < NBAR; i++) mbar_init(sb + OFF_BAR + i * 8, 1);
        asm volatile("fence.mbarrier_init.release.cluster;" ::: "memory");
        mbar_expect(sb + BAR_WQ, 65536);
        tma2d(sb + OFF_WQ, &mp.wq, h * 128 + r * 64, 0, sb + BAR_WQ);
        tma2d(sb + OFF_WQ + 32768, &mp.wq, h * 128 + r * 64, 256, sb + BAR_WQ);
        const int krow = h * 4096 + 3072 + pr * 512;
        for (int i = 0; i < 8; i++) {
            mbar_expect(sb + BAR_K + i * 8, 8192);
            tma2d(sb + OFF_K + i * 8192, &mp.k, r * 64, krow + i * 64, sb + BAR_K + i * 8);
        }
        for (int i = 0; i < 4; i++) {
            mbar_expect(sb + BAR_V + i * 8, 16384);
            tma2d(sb + OFF_V + i * 16384, &mp.v, r * 64, krow + i * 128, sb + BAR_V + i * 8);
        }
        for (int i = 0; i < 8; i++) mbar_expect(sb + BAR_SX + i * 8, 256);
    }

    unsigned char* accp;
    {
        uintptr_t base = (reinterpret_cast<uintptr_t>(g_acc_raw) + 32767) & ~(uintptr_t)32767;
        accp = reinterpret_cast<unsigned char*>(base) + w * 4096 + (g & 1) * 256 + (g >> 1) * 1024 + t * 16;
    }
    const bool own = t < 3;
    float xo[3];
#pragma unroll
    for (int i = 0; i < 3; i++) {
        const int vi = 3 * t + i;
        xo[i] = (vi < 8) ? __bfloat162float(x_in[64 * w + 8 * vi + g]) : 0.f;
    }
    if (b == NCTA - 1) {
        st_relaxed4(accp + eoff(1), 0.f, 0.f, 0.f, 0.f);
        st_relaxed4(accp + eoff(2), 0.f, 0.f, 0.f, 0.f);
        st_relaxed4(accp + eoff(3), 0.f, 0.f, 0.f, 0.f);
        __threadfence();
    }
    if (w == 1 && lane < 4) {
        st_relaxed4(&g_ml[1][b][lane * 2], 0.f, 0.f, 0.f, 0.f);
        __threadfence();
    }
    asm volatile("barrier.cluster.arrive.release.aligned;\nbarrier.cluster.wait.acquire.aligned;" ::: "memory");

    const int mi = lane >> 3, li = lane & 7;
    const uint32_t a_gemv = ((mi & 1) * 64 + (mi >> 1) * 8 + li) * 128 + ((w ^ li) << 4);
    const uint32_t a_box = sb + OFF_K + w * 8192;
    const uint32_t x_st = sb + OFF_XS + w * 128;
    const uint32_t vec_rd = (g & 1) * 128 + t * 32;
    const uint32_t vec_sw = (g & 1) << 4;
    const uint32_t qo_st = (g >> 1) * 32 + w * 4 + (g & 1) * 2;
    uint32_t peer_sx, peer_bar;
    asm("mapa.shared::cluster.u32 %0, %1, %2;" : "=r"(peer_sx) : "r"(sb + OFF_SX + tid * 8), "r"(r ^ 1));
    asm("mapa.shared::cluster.u32 %0, %1, %2;" : "=r"(peer_bar) : "r"(sb + BAR_SX + w * 8), "r"(r ^ 1));

    uint32_t Kf[16][4], Vf[16][4], S[16][4];
    float shift = 0.f, cs_q = 0.f;
    STAMP(0);

#pragma unroll 1
    for (int layer = 0; layer < 2; layer++) {
        if (layer == 0) mbar_wait(sb + BAR_WQ, 0);
#pragma unroll
        for (int j = 0; j < 16; j++) ldsm4t(S[j], sb + OFF_WQ + a_gemv + ((j >> 2) * 128 + (j & 3) * 16) * 128);
        if (layer == 1) {
            if (!ffn) poll_update(accp + eoff(0), (float)NCTA, own, xo);
            poll_update(accp + eoff(1), (float)NFFN, own, xo);
        }
        STAMP(1 + layer * 14);
#pragma unroll
        for (int i = 0; i < 3; i++)
            if (3 * t + i < 8) sts16(x_st + ((((g >> 1) * 32 + (3 * t + i) * 4 + (g & 1) * 2)) ^ ((w & 1) << 4)), __float_as_uint(xo[i]) >> 16);
        cta_sync();
        float mean, rstd;
        {
            float acc[4][4];
#pragma unroll
            for (int a = 0; a < 4; a++) acc[a][0] = acc[a][1] = acc[a][2] = acc[a][3] = 0.f;
#pragma unroll
            for (int a = 0; a < 4; a++) {
                uint4 lo = make_uint4(ONES, ONES, ONES, ONES), hi = lo;
                if (!(g & 2)) {
                    lo = lds128(sb + OFF_XS + vec_rd + a * 256 + vec_sw);
                    hi = lds128(sb + OFF_XS + vec_rd + a * 256 + (vec_sw ^ 16));
                }
                mma(acc[a], S[a * 4 + 0], lo.x, lo.y);
                mma(acc[a], S[a * 4 + 1], lo.z, lo.w);
                mma(acc[a], S[a * 4 + 2], hi.x, hi.y);
                mma(acc[a], S[a * 4 + 3], hi.z, hi.w);
            }
            ln_stats(sb, lane, shift, mean, rstd);
            if (layer == 0) ln_stats(sb, lane, mean, mean, rstd);
            shift = mean;
            float val = ((acc[0][0] + acc[0][3]) + (acc[1][0] + acc[1][3])) + ((acc[2][0] + acc[2][3]) + (acc[3][0] + acc[3][3]));
            if (layer == 0) cs_q = __shfl_xor_sync(0xffffffffu, val, 1);
            float q = fmaf(-mean, cs_q, val);
            if (t == 0) sts16(sb + OFF_QS + qo_st, pack_bf16(q, 0.f));
        }
        STAMP(2 + layer * 14);
        if (layer == 0) {
            mbar_wait(sb + BAR_K + w * 8, 0);
#pragma unroll
            for (int j = 0; j < 16; j++)
                ldsm4(Kf[j], a_box + ((j >> 2) * 16 + (mi & 1) * 8 + li) * 128 + ((((j & 3) * 2 + (mi >> 1)) ^ li) << 4));
        }
        cta_sync();
        float s0, s1;
        {
            uint4 q0 = lds128(sb + OFF_QS + t * 32), q1 = lds128(sb + OFF_QS + t * 32 + 16);
            float sc[4][4];
#pragma unroll
            for (int j = 0; j < 4; j++) {
                sc[j][0] = sc[j][1] = sc[j][2] = sc[j][3] = 0.f;
                mma(sc[j], Kf[j * 4 + 0], q0.x, q0.y);
                mma(sc[j], Kf[j * 4 + 1], q0.z, q0.w);
                mma(sc[j], Kf[j * 4 + 2], q1.x, q1.y);
                mma(sc[j], Kf[j * 4 + 3], q1.z, q1.w);
            }
            if (layer == 1) {
#pragma unroll
                for (int j = 0; j < 8; j++)
                    ldsm4t(S[j], a_box + ((j & 3) * 16 + (mi >> 1) * 8 + li) * 128 + ((((j >> 2) * 2 + (mi & 1)) ^ li) << 4));
            }
            s0 = (t & 2) ? ((t & 1) ? sc[3][0] : sc[2][0]) : ((t & 1) ? sc[1][0] : sc[0][0]);
            s1 = (t & 2) ? ((t & 1) ? sc[3][2] : sc[2][2]) : ((t & 1) ? sc[1][2] : sc[0][2]);
        }
        asm volatile("st.async.weak.shared::cluster.mbarrier::complete_tx::bytes.v2.f32 [%0], {%1,%2}, [%3];"
                     ::"r"(peer_sx), "f"(s0), "f"(s1), "r"(peer_bar) : "memory");
        STAMP(3 + layer * 14);
        if (layer == 0) {
            __syncwarp();
            if (lane == 0) {
                mbar_expect(sb + BAR_WO + w * 8, 8192);
                tma2d(a_box, &mp.wo, w * 64, h * 128 + r * 64, sb + BAR_WO + w * 8);
            }
        } else {
#pragma unroll
            for (int j = 8; j < 16; j++)
                ldsm4t(S[j], a_box + ((j & 3) * 16 + (mi >> 1) * 8 + li) * 128 + ((((j >> 2) * 2 + (mi & 1)) ^ li) << 4));
        }
        mbar_wait_cluster(sb + BAR_SX + w * 8, layer);
        float mw, lw;
        {
            float2 o2 = lds64f(sb + OFF_SX + tid * 8);
            const float scl = rstd * (0.08838834764831845f * 1.4426950408889634f);
            s0 = (s0 + o2.x) * scl;
            s1 = (s1 + o2.y) * scl;
            int mi_ = __float_as_int(fmaxf(s0, s1));
            mi_ ^= (mi_ >> 31) & 0x7fffffff;
            mi_ = __reduce_max_sync(0xffffffffu, mi_);
            mi_ ^= (mi_ >> 31) & 0x7fffffff;
            mw = fmaxf(__int_as_float(mi_), -3.0e38f);
            uint32_t pp = pack_bf16(ex2(s0 - mw), ex2(s1 - mw));
            const uint32_t pa = sb + OFF_PS + w * 128 + (((g >> 1) * 32 + t * 8 + (g & 1) * 2) ^ ((w & 1) << 4));
            sts16(pa, pp & 0xffffu);
            sts16(pa + 4, pp >> 16);
            if (lane == 0) sts32f(sb + OFF_M + w * 4, mw);
            lw = __uint_as_float(pp << 16) + __uint_as_float(pp & 0xffff0000u);
        }
        STAMP(4 + layer * 14);
        cta_sync();
        if (layer == 0 && lane == 0) mbar_expect(sb + BAR_SX + w * 8, 256);
        float M;
        float2 rem = make_float2(0.f, 0.f);
        {
#pragma unroll
            for (int o = 16; o > 0; o >>= 1) lw += __shfl_xor_sync(0xffffffffu, lw, o);
            if (lane == 0) {
                st_relaxed2(&g_ml[layer][b][w], mw, __uint_as_float(__float_as_uint(lw) | 0x80000000u));
                sts32f(sb + OFF_L + w * 4, lw);
                if (layer == 1) st_relaxed2(&g_ml[0][b][w], 0.f, 0.f);
            }
            if (layer == 0) {
                int n = 0;
                do { rem = ld_relaxed2(&g_ml[0][b ^ 2][li]); } while (!__all_sync(0xffffffffu, __float_as_uint(rem.y) != 0u) && ++n < SPIN_LIMIT);
            }
            float acc[4][4];
#pragma unroll
            for (int a = 0; a < 4; a++) {
                if (layer == 0) {
                    mbar_wait(sb + BAR_V + a * 8, 0);
#pragma unroll
                    for (int j = 0; j < 4; j++) ldsm4t(Vf[a * 4 + j], sb + OFF_V + a_gemv + (a * 128 + j * 16) * 128);
                }
                uint4 lo = lds128(sb + OFF_PS + vec_rd + a * 256 + vec_sw);
                uint4 hi = lds128(sb + OFF_PS + vec_rd + a * 256 + (vec_sw ^ 16));
                acc[a][0] = acc[a][1] = acc[a][2] = acc[a][3] = 0.f;
                mma(acc[a], Vf[a * 4 + 0], lo.x, lo.y);
                mma(acc[a], Vf[a * 4 + 1], lo.z, lo.w);
                mma(acc[a], Vf[a * 4 + 2], hi.x, hi.y);
                mma(acc[a], Vf[a * 4 + 3], hi.z, hi.w);
            }
            float4 m0 = lds128f(sb + OFF_M), m1 = lds128f(sb + OFF_M + 16);
            M = fmaxf(fmaxf(fmaxf(m0.x, m0.y), fmaxf(m0.z, m0.w)), fmaxf(fmaxf(m1.x, m1.y), fmaxf(m1.z, m1.w)));
            float o = ((ex2(m0.x - M) * acc[0][0] + ex2(m0.y - M) * acc[0][3]) + (ex2(m0.z - M) * acc[1][0] + ex2(m0.w - M) * acc[1][3])) +
                      ((ex2(m1.x - M) * acc[2][0] + ex2(m1.y - M) * acc[2][3]) + (ex2(m1.z - M) * acc[3][0] + ex2(m1.w - M) * acc[3][3]));
            if (t == 0) sts16(sb + OFF_OS + qo_st, pack_bf16(o, 0.f));
        }
        STAMP(5 + layer * 14);
        cta_sync();
        if (layer == 0) {
            if (tid == 0 && ffn) {
                mbar_expect(sb + BAR_W13, 32768);
                tma2d(sb + OFF_W1, &mp.w1, b * 16, 0, sb + BAR_W13);
                tma2d(sb + OFF_W3, &mp.w3, b * 16, 0, sb + BAR_W13);
                tma2d(sb + OFF_W1 + 8192, &mp.w1, b * 16, 256, sb + BAR_W13);
                tma2d(sb + OFF_W3 + 8192, &mp.w3, b * 16, 256, sb + BAR_W13);
                mbar_expect(sb + BAR_W2, 16384);
                for (int i = 0; i < 8; i++) tma2d(sb + OFF_W2 + i * 2048, &mp.w2, i * 64, b * 16, sb + BAR_W2);
            }
            mbar_wait(sb + BAR_WO + w * 8, 0);
#pragma unroll
            for (int j = 0; j < 16; j++)
                ldsm4t(S[j], a_box + ((j & 3) * 16 + (mi >> 1) * 8 + li) * 128 + ((((j >> 2) * 2 + (mi & 1)) ^ li) << 4));
        } else {
            rem = ld_relaxed2(&g_ml[1][b ^ 2][li]);
        }
        {
            uint4 o0 = lds128(sb + OFF_OS + t * 32), o1 = lds128(sb + OFF_OS + t * 32 + 16);
            float mo = lds32f(sb + OFF_M + li * 4), lo_ = lds32f(sb + OFF_L + li * 4);
            float y[4][4];
#pragma unroll
            for (int j = 0; j < 4; j++) {
                y[j][0] = y[j][1] = y[j][2] = y[j][3] = 0.f;
                mma(y[j], S[j * 4 + 0], o0.x, o0.y);
                mma(y[j], S[j * 4 + 1], o0.z, o0.w);
                mma(y[j], S[j * 4 + 2], o1.x, o1.y);
                mma(y[j], S[j * 4 + 3], o1.z, o1.w);
            }
            float tot = lo_ * ex2(mo - M);
            STAMP(6 + layer * 14);
            if (layer == 1) {
                int n = 0;
                while (!__all_sync(0xffffffffu, __float_as_uint(rem.y) != 0u) && ++n < SPIN_LIMIT) rem = ld_relaxed2(&g_ml[1][b ^ 2][li]);
            }
            tot = fmaf(-rem.y, ex2(rem.x - M), tot);
            tot += __shfl_xor_sync(0xffffffffu, tot, 1);
            tot += __shfl_xor_sync(0xffffffffu, tot, 2);
            tot += __shfl_xor_sync(0xffffffffu, tot, 4);
            const float inv = rcp(tot);
            float v0 = (t == 0) ? y[0][0] : (t == 1) ? y[1][2] : y[3][0];
            float v1 = (t == 0) ? y[0][2] : (t == 1) ? y[2][0] : y[3][2];
            float v2 = (t == 0) ? y[1][0] : (t == 1) ? y[2][2] : 0.f;
            if (own) red4(accp + (layer ? eoff(2) : eoff(0)), v0 * inv, v1 * inv, v2 * inv, 1.f);
        }
        STAMP(7 + layer * 14);

        if (ffn) {
            if (layer == 0) mbar_wait(sb + BAR_W13, 0);
            {
                const uint32_t base = sb + ((mi & 1) ? OFF_W3 : OFF_W1) + ((w >> 1) * 128 + (mi >> 1) * 8 + li) * 32 + (((w & 1) ^ (li >> 2)) << 4);
#pragma unroll
                for (int j = 0; j < 8; j++) ldsm4t(S[j], base + j * 16 * 32);
            }
            if (layer == 1) {
#pragma unroll
                for (int j = 0; j < 4; j++)
                    ldsm4t(S[8 + j], sb + OFF_W2 + w * 2048 + ((mi >> 1) * 8 + li) * 128 + (((j * 2 + (mi & 1)) ^ li) << 4));
            }
            STAMP(8 + layer * 14);
            poll_update(accp + (layer ? eoff(2) : eoff(0)), (float)NCTA, own, xo);
            STAMP(9 + layer * 14);
#pragma unroll
            for (int i = 0; i < 3; i++)
                if (3 * t + i < 8) sts16(x_st + ((((g >> 1) * 32 + (3 * t + i) * 4 + (g & 1) * 2)) ^ ((w & 1) << 4)), __float_as_uint(xo[i]) >> 16);
            if (layer == 1 && b == 0) st_relaxed4(accp + eoff(0), 0.f, 0.f, 0.f, 0.f);
            cta_sync();
            {
                float acc[2][4];
#pragma unroll
                for (int a = 0; a < 2; a++) {
                    uint4 lo = make_uint4(ONES, ONES, ONES, ONES), hi = lo;
                    if (!(g & 1)) {
                        lo = lds128(sb + OFF_XS + (w >> 1) * 256 + a * 128 + t * 32 + (a << 4));
                        hi = lds128(sb + OFF_XS + (w >> 1) * 256 + a * 128 + t * 32 + ((a ^ 1) << 4));
                    }
                    acc[a][0] = acc[a][1] = acc[a][2] = acc[a][3] = 0.f;
                    mma(acc[a], S[a * 4 + 0], lo.x, lo.y);
                    mma(acc[a], S[a * 4 + 1], lo.z, lo.w);
                    mma(acc[a], S[a * 4 + 2], hi.x, hi.y);
                    mma(acc[a], S[a * 4 + 3], hi.z, hi.w);
                }
                if (t == 0) sts128f(sb + OFF_FP + (w * 8 + g) * 16, acc[0][0] + acc[1][0], acc[0][1] + acc[1][1], acc[0][2] + acc[1][2], acc[0][3] + acc[1][3]);
            }
            float mean2, rstd2;
            ln_stats(sb, lane, shift, mean2, rstd2);
            shift = mean2;
            STAMP(10 + layer * 14);
            cta_sync();
            {
                const uint32_t fa = sb + OFF_FP + (lane & 15) * 16;
                float4 p0 = lds128f(fa), p1 = lds128f(fa + 256), p2 = lds128f(fa + 512), p3 = lds128f(fa + 768);
                float gd = (p0.x + p1.x) + (p2.x + p3.x), gc = (p0.y + p1.y) + (p2.y + p3.y);
                float ud = (p0.z + p1.z) + (p2.z + p3.z), uc = (p0.w + p1.w) + (p2.w + p3.w);
                float gate = rstd2 * fmaf(-mean2, gc, gd), up = rstd2 * fmaf(-mean2, uc, ud);
                float hv = gate * rcp(1.f + ex2(-1.4426950408889634f * gate)) * up;
                float h0 = __shfl_sync(0xffffffffu, hv, 2 * t), h1 = __shfl_sync(0xffffffffu, hv, 2 * t + 1);
                float h2 = __shfl_sync(0xffffffffu, hv, 2 * t + 8), h3 = __shfl_sync(0xffffffffu, hv, 2 * t + 9);
                const uint32_t b0 = pack_bf16(h0, h1), b1 = pack_bf16(h2, h3);
                if (layer == 0) {
                    mbar_wait(sb + BAR_W2, 0);
#pragma unroll
                    for (int j = 0; j < 4; j++)
                        ldsm4t(S[8 + j], sb + OFF_W2 + w * 2048 + ((mi >> 1) * 8 + li) * 128 + (((j * 2 + (mi & 1)) ^ li) << 4));
                }
                float y[4][4];
#pragma unroll
                for (int j = 0; j < 4; j++) {
                    y[j][0] = y[j][1] = y[j][2] = y[j][3] = 0.f;
                    mma(y[j], S[8 + j], b0, b1);
                }
                float v0 = (t == 0) ? y[0][0] : (t == 1) ? y[1][2] : y[3][0];
                float v1 = (t == 0) ? y[0][2] : (t == 1) ? y[2][0] : y[3][2];
                float v2 = (t == 0) ? y[1][0] : (t == 1) ? y[2][2] : 0.f;
                STAMP(11 + layer * 14);
                if (layer == 0) {
                    if (own) red4(accp + eoff(1), v0, v1, v2, 1.f);
                } else if (own) {
                    float4 old = atom4(accp + eoff(3), v0, v1, v2, 1.f);
                    if (old.w == (float)(NFFN - 1)) {
                        const int c = 64 * w + 24 * t + g;
                        out[c] = __float2bfloat16(xo[0] + bf16r(old.x + v0));
                        out[c + 8] = __float2bfloat16(xo[1] + bf16r(old.y + v1));
                        if (t < 2) out[c + 16] = __float2bfloat16(xo[2] + bf16r(old.z + v2));
                    }
                }
            }
            STAMP(12 + layer * 14);
        }
    }
}

typedef CUresult (*EncodeFn)(CUtensorMap*, CUtensorMapDataType, cuuint32_t, void*, const cuuint64_t*, const cuuint64_t*,
                             const cuuint32_t*, const cuuint32_t*, CUtensorMapInterleave, CUtensorMapSwizzle,
                             CUtensorMapL2promotion, CUtensorMapFloatOOBfill);

void make_map(EncodeFn enc, CUtensorMap* m, const void* p, uint64_t cols, uint64_t rows, uint32_t bc, uint32_t br) {
    cuuint64_t gd[2] = {cols, rows};
    cuuint64_t gs[1] = {cols * 2};
    cuuint32_t bd[2] = {bc, br};
    cuuint32_t es[2] = {1, 1};
    enc(m, CU_TENSOR_MAP_DATA_TYPE_BFLOAT16, 2, const_cast<void*>(p), gd, gs, bd, es, CU_TENSOR_MAP_INTERLEAVE_NONE,
        bc == 64 ? CU_TENSOR_MAP_SWIZZLE_128B : CU_TENSOR_MAP_SWIZZLE_32B, CU_TENSOR_MAP_L2_PROMOTION_NONE,
        CU_TENSOR_MAP_FLOAT_OOB_FILL_NONE);
}

}

extern "C" void kernel_launch(void* const* d_in, const int* in_sizes, int n_in, void* d_out, int out_size) {
    (void)in_sizes; (void)n_in; (void)out_size;
    static EncodeFn enc = nullptr;
    if (!enc) {
        cudaDriverEntryPointQueryResult qr;
        void* fn = nullptr;
        cudaGetDriverEntryPoint("cuTensorMapEncodeTiled", &fn, cudaEnableDefault, &qr);
        enc = (EncodeFn)fn;
        cudaFuncSetAttribute(fused_kernel, cudaFuncAttributeMaxDynamicSharedMemorySize, (int)SMEM_BYTES);
    }
    Maps mp;
    make_map(enc, &mp.wq, d_in[3], 4096, 512, 64, 256);
    make_map(enc, &mp.k, d_in[1], 128, 32 * 4096, 64, 64);
    make_map(enc, &mp.v, d_in[2], 128, 32 * 4096, 64, 128);
    make_map(enc, &mp.wo, d_in[4], 512, 4096, 64, 64);
    make_map(enc, &mp.w1, d_in[6], 1376, 512, 16, 256);
    make_map(enc, &mp.w3, d_in[7], 1376, 512, 16, 256);
    make_map(enc, &mp.w2, d_in[8], 512, 1376, 64, 16);
    fused_kernel<<<NCTA, NTHR, SMEM_BYTES>>>(mp, (const __nv_bfloat16*)d_in[0], (__nv_bfloat16*)d_out);
}
```

```cpp
#include <cuda_runtime.h>
#include <cuda_bf16.h>
#include <cuda.h>
#include <stdint.h>

namespace {

constexpr int NCTA = 128;
constexpr int NTHR = 256;
constexpr int NFFN = 86;
#define TWO 11000u
#define NWO1 8
#define NWO2 10
#define NWO3 12
#define PD2 600u
#define PD3 600u
#define PDN 900u
#define TW13 13500u
constexpr int SPIN_LIMIT = 1 << 22;

constexpr uint32_t OFF_WQ = 0;
constexpr uint32_t OFF_K = 65536;
constexpr uint32_t OFF_W13 = OFF_K + 5 * 8192;
constexpr uint32_t OFF_SX0 = OFF_K + 65536;
constexpr uint32_t OFF_WO5 = OFF_SX0 + 8192;
constexpr uint32_t OFF_V = OFF_WO5 + 24576;
constexpr uint32_t OFF_W2 = OFF_V;
constexpr uint32_t OFF_SX1 = OFF_V + 16384;
constexpr uint32_t OFF_FP = OFF_SX1 + 2048;
constexpr uint32_t OFF_FC = OFF_FP + 512;
constexpr uint32_t VS = 144;
constexpr uint32_t OFF_XS = OFF_V + 65536;
constexpr uint32_t OFF_PS = OFF_XS + 1152;
constexpr uint32_t OFF_QS = OFF_PS + 1152;
constexpr uint32_t OFF_OS = OFF_QS + 128;
constexpr uint32_t OFF_M = OFF_OS + 128;
constexpr uint32_t OFF_SQ = OFF_M + 32;
constexpr uint32_t OFF_BAR = OFF_SQ + 32;
constexpr uint32_t BS = 48;
constexpr uint32_t B_WQ = 0, B_K = 8, B_V = 16, B_WO = 24, B_F = 32, B_SX = 40;
constexpr uint32_t SMEM_BYTES = OFF_BAR + 8 * BS;
static_assert(SMEM_BYTES <= 232448, "smem");

struct Maps { CUtensorMap wq, k, v, wo, w1, w3, w2; };

typedef float2 MlRow[NCTA][16];
__device__ __align__(128) unsigned char g_acc_raw[65536];
__device__ __align__(128) float2 g_ml_buf[2][NCTA][16];
#define PROF_PARAM
#define STAMP(k) do {} while (0)

__device__ __forceinline__ void mbar_init(uint32_t a, int c) {
    asm volatile("mbarrier.init.shared::cta.b64 [%0], %1;" ::"r"(a), "r"(c) : "memory");
}
__device__ __forceinline__ void mbar_expect(uint32_t a, uint32_t bytes) {
    asm volatile("mbarrier.arrive.expect_tx.shared::cta.b64 _, [%0], %1;" ::"r"(a), "r"(bytes) : "memory");
}
__device__ __forceinline__ void mbar_wait(uint32_t a, uint32_t parity) {
    uint32_t ok;
    int n = 0;
    do {
        asm volatile("{\n.reg .pred p;\nmbarrier.try_wait.parity.shared::cta.b64 p, [%1], %2;\nselp.u32 %0, 1, 0, p;\n}"
                     : "=r"(ok) : "r"(a), "r"(parity) : "memory");
    } while (!ok && ++n < SPIN_LIMIT);
}
__device__ __forceinline__ void mbar_wait_cluster(uint32_t a, uint32_t parity) {
    uint32_t ok;
    int n = 0;
    do {
        asm volatile("{\n.reg .pred p;\nmbarrier.try_wait.parity.acquire.cluster.shared::cta.b64 p, [%1], %2;\nselp.u32 %0, 1, 0, p;\n}"
                     : "=r"(ok) : "r"(a), "r"(parity) : "memory");
    } while (!ok && ++n < SPIN_LIMIT);
}
__device__ __forceinline__ void tma2d(uint32_t dst, const CUtensorMap* m, int c0, int c1, uint32_t bar) {
    asm volatile("cp.async.bulk.tensor.2d.shared::cluster.global.mbarrier::complete_tx::bytes [%0], [%1, {%3, %4}], [%2];"
                 ::"r"(dst), "l"(m), "r"(bar), "r"(c0), "r"(c1) : "memory");
}
__device__ __forceinline__ void ldsm4(uint32_t* r, uint32_t a) {
    asm volatile("ldmatrix.sync.aligned.m8n8.x4.shared.b16 {%0,%1,%2,%3}, [%4];"
                 : "=r"(r[0]), "=r"(r[1]), "=r"(r[2]), "=r"(r[3]) : "r"(a) : "memory");
}
__device__ __forceinline__ void ldsm4t(uint32_t* r, uint32_t a) {
    asm volatile("ldmatrix.sync.aligned.m8n8.x4.trans.shared.b16 {%0,%1,%2,%3}, [%4];"
                 : "=r"(r[0]), "=r"(r[1]), "=r"(r[2]), "=r"(r[3]) : "r"(a) : "memory");
}
__device__ __forceinline__ void mma(float* c, const uint32_t* a, uint32_t b0, uint32_t b1) {
    asm("mma.sync.aligned.m16n8k16.row.col.f32.bf16.bf16.f32 {%0,%1,%2,%3},{%4,%5,%6,%7},{%8,%9},{%0,%1,%2,%3};"
        : "+f"(c[0]), "+f"(c[1]), "+f"(c[2]), "+f"(c[3])
        : "r"(a[0]), "r"(a[1]), "r"(a[2]), "r"(a[3]), "r"(b0), "r"(b1));
}
__device__ __forceinline__ uint4 lds128(uint32_t a) {
    uint4 v;
    asm volatile("ld.shared.v4.u32 {%0,%1,%2,%3}, [%4];" : "=r"(v.x), "=r"(v.y), "=r"(v.z), "=r"(v.w) : "r"(a) : "memory");
    return v;
}
__device__ __forceinline__ float4 lds128f(uint32_t a) {
    float4 v;
    asm volatile("ld.shared.v4.f32 {%0,%1,%2,%3}, [%4];" : "=f"(v.x), "=f"(v.y), "=f"(v.z), "=f"(v.w) : "r"(a) : "memory");
    return v;
}
__device__ __forceinline__ float2 lds64f(uint32_t a) {
    float2 v;
    asm volatile("ld.shared.v2.f32 {%0,%1}, [%2];" : "=f"(v.x), "=f"(v.y) : "r"(a) : "memory");
    return v;
}
__device__ __forceinline__ float lds32f(uint32_t a) {
    float v;
    asm volatile("ld.shared.f32 %0, [%1];" : "=f"(v) : "r"(a) : "memory");
    return v;
}
__device__ __forceinline__ void sts16(uint32_t a, uint32_t v) {
    asm volatile("st.shared.u16 [%0], %1;" ::"r"(a), "h"((unsigned short)v) : "memory");
}
__device__ __forceinline__ void sts32f(uint32_t a, float v) {
    asm volatile("st.shared.f32 [%0], %1;" ::"r"(a), "f"(v) : "memory");
}
__device__ __forceinline__ void sts128f(uint32_t a, float x, float y, float z, float w) {
    asm volatile("st.shared.v4.f32 [%0], {%1,%2,%3,%4};" ::"r"(a), "f"(x), "f"(y), "f"(z), "f"(w) : "memory");
}
__device__ __forceinline__ void cta_sync() { asm volatile("bar.sync 0;" ::: "memory"); }
__device__ __forceinline__ float ex2(float x) {
    float y;
    asm("ex2.approx.ftz.f32 %0, %1;" : "=f"(y) : "f"(x));
    return y;
}
__device__ __forceinline__ float rcp(float x) {
    float y;
    asm("rcp.approx.ftz.f32 %0, %1;" : "=f"(y) : "f"(x));
    return y;
}
__device__ __forceinline__ uint32_t pack_bf16(float lo, float hi) {
    uint32_t r;
    asm("cvt.rn.bf16x2.f32 %0, %1, %2;" : "=r"(r) : "f"(hi), "f"(lo));
    return r;
}
__device__ __forceinline__ float bf16r(float x) { return __uint_as_float(pack_bf16(0.f, x) & 0xffff0000u); }
__device__ __forceinline__ float4 ld_relaxed4(const void* p) {
    float4 v;
    asm volatile("ld.relaxed.gpu.global.v4.f32 {%0,%1,%2,%3}, [%4];" : "=f"(v.x), "=f"(v.y), "=f"(v.z), "=f"(v.w) : "l"(p) : "memory");
    return v;
}
__device__ __forceinline__ float2 ld_relaxed2(const void* p) {
    float2 v;
    asm volatile("ld.relaxed.gpu.global.v2.f32 {%0,%1}, [%2];" : "=f"(v.x), "=f"(v.y) : "l"(p) : "memory");
    return v;
}
__device__ __forceinline__ void st_relaxed2(void* p, float x, float y) {
    asm volatile("st.relaxed.gpu.global.v2.f32 [%0], {%1,%2};" ::"l"(p), "f"(x), "f"(y) : "memory");
}
__device__ __forceinline__ void st_relaxed4(void* p, float x, float y, float z, float w) {
    asm volatile("st.relaxed.gpu.global.v4.f32 [%0], {%1,%2,%3,%4};" ::"l"(p), "f"(x), "f"(y), "f"(z), "f"(w) : "memory");
}
__device__ __forceinline__ void red4(void* p, float x, float y, float z, float w) {
    asm volatile("red.relaxed.gpu.global.add.v4.f32 [%0], {%1,%2,%3,%4};" ::"l"(p), "f"(x), "f"(y), "f"(z), "f"(w) : "memory");
}
__device__ __forceinline__ float4 atom4(void* p, float x, float y, float z, float w) {
    float4 v;
    asm volatile("atom.relaxed.gpu.global.add.v4.f32 {%0,%1,%2,%3}, [%4], {%5,%6,%7,%8};"
                 : "=f"(v.x), "=f"(v.y), "=f"(v.z), "=f"(v.w) : "l"(p), "f"(x), "f"(y), "f"(z), "f"(w) : "memory");
    return v;
}
__device__ __forceinline__ constexpr uint32_t eoff(int e) { return (uint32_t)((e & 1) * 128 + (e >> 1) * 512); }

constexpr uint32_t ONES = 0x3F803F80u;

__device__ __forceinline__ void mma_ab(float* c, uint32_t a0, uint32_t a1, uint32_t a2, uint32_t a3, uint32_t b0, uint32_t b1) {
    asm("mma.sync.aligned.m16n8k16.row.col.f32.bf16.bf16.f32 {%0,%1,%2,%3},{%4,%5,%6,%7},{%8,%9},{%0,%1,%2,%3};"
        : "+f"(c[0]), "+f"(c[1]), "+f"(c[2]), "+f"(c[3])
        : "r"(a0), "r"(a1), "r"(a2), "r"(a3), "r"(b0), "r"(b1));
}
__device__ __forceinline__ bool elect_one() {
    uint32_t p;
    asm volatile("{\n.reg .pred p;\nelect.sync _|p, 0xffffffff;\nselp.u32 %0, 1, 0, p;\n}" : "=r"(p));
    return p;
}
__device__ __forceinline__ float rsq(float x) {
    float y;
    asm("rsqrt.approx.ftz.f32 %0, %1;" : "=f"(y) : "f"(x));
    return y;
}
__device__ __forceinline__ uint32_t elapsed(uint32_t c0) {
    uint32_t c;
    asm volatile("mov.u32 %0, %%clock;" : "=r"(c) :: "memory");
    return __shfl_sync(0xffffffffu, c, 0) - c0 ;
}
__device__ __forceinline__ void zero4(float* c) { c[0] = c[1] = c[2] = c[3] = 0.f; }
__device__ __forceinline__ uint32_t pin(uint32_t v, int lane) { return __shfl_sync(0xffffffffu, v, lane); }

__device__ __forceinline__ void ln_partials(const uint4& u0, const uint4& u1, bool godd, float& s, float& q) {
    float c[4], d[4];
    zero4(c); zero4(d);
    mma_ab(c, u0.x, ONES, u0.y, ONES, u0.x, u0.y);
    mma_ab(d, u1.x, ONES, u1.y, ONES, u1.x, u1.y);
    mma_ab(c, u0.z, ONES, u0.w, ONES, u0.z, u0.w);
    mma_ab(d, u1.z, ONES, u1.w, ONES, u1.z, u1.w);
    s = (c[2] + d[2]) + (c[3] + d[3]);
    q = godd ? c[1] + d[1] : c[0] + d[0];
}
__device__ __forceinline__ void ln_finish(float s, float q, float& mean, float& rstd) {
    q += __shfl_xor_sync(0xffffffffu, q, 4);
    s += __shfl_xor_sync(0xffffffffu, s, 1);
    q += __shfl_xor_sync(0xffffffffu, q, 9);
    s += __shfl_xor_sync(0xffffffffu, s, 2);
    q += __shfl_xor_sync(0xffffffffu, q, 18);
    mean = s * (1.f / 512.f);
    q = __shfl_sync(0xffffffffu, q, 0);
    rstd = rsq(fmaxf(fmaf(-mean, mean, q * (1.f / 512.f)), 0.f) + 1e-5f);
}

__device__ __forceinline__ bool cta_sync_and(bool p) {
    uint32_t r;
    asm volatile("{\n.reg .pred p, q;\nsetp.ne.u32 p, %1, 0;\nbar.red.and.pred q, 0, p;\nselp.u32 %0, 1, 0, q;\n}" : "=r"(r) : "r"((uint32_t)p) : "memory");
    return r;
}
#define FENCE() __syncwarp()

__global__ void __cluster_dims__(2, 1, 1) __launch_bounds__(NTHR, 1)
fused_kernel(const __nv_bfloat16* __restrict__ x_in, __nv_bfloat16* __restrict__ out, unsigned char* const acc_base, MlRow* const g_ml,
             PROF_PARAM const __grid_constant__ Maps mp) {
    extern __shared__ __align__(1024) unsigned char smem[];
    const uint32_t sb = (uint32_t)__cvta_generic_to_shared(smem);
    const int tid = threadIdx.x;
    const int b = blockIdx.x, r = b & 1, pr = (b >> 1) & 1, h = b >> 2;
    unsigned clk0;
    asm volatile("mov.u32 %0, %%clock;" : "=r"(clk0) :: "memory");
    if (tid == 0) {
        mbar_init(sb + OFF_BAR + B_WQ, 1);
        asm volatile("fence.mbarrier_init.release.cluster;" ::: "memory");
        mbar_expect(sb + OFF_BAR + B_WQ, 65536 + 1024);
        asm volatile("cp.async.bulk.shared::cluster.global.mbarrier::complete_tx::bytes [%0], [%1], 1024, [%2];"
                     ::"r"(sb + OFF_PS), "l"(x_in), "r"(sb + OFF_BAR + B_WQ) : "memory");
        tma2d(sb + OFF_WQ, &mp.wq, h * 128 + r * 64, 0, sb + OFF_BAR + B_WQ);
        tma2d(sb + OFF_WQ + 32768, &mp.wq, h * 128 + r * 64, 256, sb + OFF_BAR + B_WQ);
        const int kr = h * 4096 + 3072 + pr * 512;
#pragma unroll
        for (int i = 0; i < 4; i++) { mbar_init(sb + OFF_BAR + i * BS + B_K, 1); mbar_init(sb + OFF_BAR + i * BS + B_V, 1); }
        asm volatile("fence.mbarrier_init.release.cluster;" ::: "memory");
#pragma unroll
        for (int i = 0; i < 4; i++) {
            mbar_expect(sb + OFF_BAR + i * BS + B_K, 16384);
            tma2d(sb + OFF_K + i * 16384, &mp.k, r * 64, kr + i * 128, sb + OFF_BAR + i * BS + B_K);
        }
#pragma unroll
        for (int i = 0; i < 4; i++) {
            mbar_expect(sb + OFF_BAR + i * BS + B_V, 16384);
            tma2d(sb + OFF_V + i * 16384, &mp.v, r * 64, kr + i * 128, sb + OFF_BAR + i * BS + B_V);
        }
    }
    clk0 = __shfl_sync(0xffffffffu, clk0, 0);
    const int w = __shfl_sync(0xffffffffu, tid >> 5, 0), lane = tid & 31, g = lane >> 2, t = lane & 3;
    const bool ffn = b < NFFN;
    const uint32_t bars = sb + OFF_BAR + w * BS;
    if (elect_one()) {
        if (w >= 1 && w < 7) asm volatile("prefetch.tensormap [%0];" ::"l"(&mp.wq + w) : "memory");
        mbar_init(bars + B_WO, 1); mbar_init(bars + B_F, 1); mbar_init(bars + B_SX, 1);
        asm volatile("fence.mbarrier_init.release.cluster;" ::: "memory");
        mbar_expect(bars + B_SX, 256);
    }
    __syncwarp();
    STAMP(13);
    asm volatile("barrier.cluster.arrive.relaxed.aligned;" ::: "memory");

    unsigned char* const accp = acc_base + pin(w * 4096 + (g >> 1) * 1024 + ((g & 1) * 3 + (t < 3 ? t : 2)) * 16, lane);
    unsigned char* const accw = accp + r * 256;
    const bool own = t < 3;
    uint32_t zdep = 0;
    {
        const int z = tid - 32;
        unsigned char* zp;
        if (z < 16) zp = reinterpret_cast<unsigned char*>(&g_ml[1][b][0]) + z * 4;
        else {
            const int i = b * 48 + (z - 16), e = 1 + (i >> 11), u = (i >> 5) & 63;
            zp = acc_base + (u >> 3) * 4096 + (u & 1) * 256 + ((u >> 1) & 3) * 1024 + (e & 1) * 128 + (e >> 1) * 512 + (i & 31) * 4;
        }
        asm volatile("{\n.reg .pred p;\nsetp.lt.u32 p, %2, 64;\n@p atom.relaxed.gpu.global.exch.b32 %0, [%1], 0;\n}"
                     : "+r"(zdep) : "l"(zp), "r"(z) : "memory");
    }

    const int mi = lane >> 3, li = lane & 7;
    const uint32_t wo_box = sb + (w < 5 ? OFF_K + w * 8192 : OFF_WO5 + (w - 5) * 8192);
    const uint32_t a_gemv = pin(sb + ((mi & 1) * 64 + (mi >> 1) * 8 + li) * 128 + ((w ^ li) << 4), lane);
    const uint32_t a_wo = pin(wo_box + ((mi >> 1) * 8 + li) * 128 + (((mi & 1) ^ li) << 4), lane);
    const uint32_t a_xst = pin(sb + OFF_XS + w * VS + (g >> 1) * 32 + (g & 1) * 2 + t * 12, lane);
    const uint32_t a_pst = pin(sb + OFF_PS + w * VS + (g >> 1) * 32 + (g & 1) * 2 + t * 8, lane);
    const uint32_t a_row = pin(sb + g * VS + t * 32, lane);
    const uint32_t a_qo = pin(sb + (g >> 1) * 32 + w * 4 + (g & 1) * 2, lane);
    const uint32_t a_t32 = pin(sb + t * 32, lane);
    const uint32_t a_sx = pin(sb + tid * 8, lane);
    uint32_t peer_sx, peer_bar;
    asm volatile("mapa.shared::cluster.u32 %0, %1, %2;" : "=r"(peer_sx) : "r"(a_sx), "r"(r ^ 1));
    asm volatile("mapa.shared::cluster.u32 %0, %1, %2;" : "=r"(peer_bar) : "r"(bars + B_SX), "r"(r ^ 1));
    float2* const mlp = &g_ml[0][b ^ 2][0] + pin(g, lane);
    float2* const mlo = &g_ml[0][0][0] + pin(b * 16 + g, lane);
    const uint32_t a_mg = pin(sb + OFF_M + g * 4, lane), a_mt = pin(sb + OFF_M + t * 8, lane), a_sb = pin(sb, lane), a_bsx = pin(bars + B_SX, lane);

    bool w13_todo = ffn && w < 4;
    auto issue_w13 = [&]() {
        if (elect_one()) {
            mbar_expect(bars + B_F, 8192);
            tma2d(sb + OFF_W13 + w * 8192, (w & 1) ? &mp.w3 : &mp.w1, b * 16, (w >> 1) * 256, bars + B_F);
        }
        __syncwarp();
    };
    uint32_t Kf[16][4], Vf[16][4], S[16][4];
    float cs_q = 0.f, cs_g = 0.f, cs_u = 0.f;
    STAMP(0);
    asm volatile("barrier.cluster.wait.acquire.aligned;" ::: "memory");
    if (w >= 5 && elect_one()) {
        mbar_expect(bars + B_WO, 8192);
        tma2d(wo_box, &mp.wo, w * 64, h * 128 + r * 64, bars + B_WO);
    }
    __syncwarp();
    mbar_wait(sb + OFF_BAR + B_WQ, 0);
    STAMP(14);
    float xo[3];
#pragma unroll
    for (int i = 0; i < 3; i++) {
        uint32_t xr;
        asm volatile("ld.shared.u16 %0, [%1];" : "=r"(xr) : "r"(sb + OFF_PS + (64 * w + 8 * ((3 * t + i) & 7) + g) * 2) : "memory");
        xo[i] = __uint_as_float(xr << 16);
    }

    auto put_x = [&](const float4& v) {
        const uint32_t p01 = pack_bf16(xo[0] + v.x, xo[1] + v.y), p2 = pack_bf16(xo[2] + v.z, 0.f);
        if (own) { sts16(a_xst, p01); sts16(a_xst + 4, p01 >> 16); }
        if (t < 2) sts16(a_xst + 8, p2);
        cta_sync();
        xo[0] = __uint_as_float(p01 << 16); xo[1] = __uint_as_float(p01 & 0xffff0000u); xo[2] = __uint_as_float(p2 << 16);
    };
    uint32_t t_red = 0;
    auto exchange_wait = [&](const unsigned char* p, float target, uint32_t delay) {
        int n = SPIN_LIMIT;
        if (delay) while (elapsed(t_red) < delay) {}
        float4 v, v2;
        do { v = ld_relaxed4(p); v2 = ld_relaxed4(p + 256); } while (__any_sync(0xffffffffu, v.w + v2.w != target) && --n > 0);
        put_x(make_float4(v.x + v2.x, v.y + v2.y, v.z + v2.z, 0.f));
    };

#pragma unroll
    for (int layer = 0; layer < 2; layer++) {
#pragma unroll
        for (int j = 0; j < 16; j++) ldsm4t(S[j], a_gemv + OFF_WQ + ((j >> 2) * 128 + (j & 3) * 16) * 128);
        if (layer == 0) {
            float c0[4], c1[4];
            zero4(c0); zero4(c1);
#pragma unroll
            for (int j = 0; j < 8; j++) { mma(c0, S[2 * j], ONES, ONES); mma(c1, S[2 * j + 1], ONES, ONES); }
            cs_q = ((c0[0] + c0[3]) + (c1[0] + c1[3])) * (1.f / 512.f);
            put_x(make_float4(0.f, 0.f, 0.f, 0.f));
        } else {
            if (!ffn) { exchange_wait(accp + eoff(0), (float)NCTA, 0); t_red = elapsed(0) + PDN; if (PDN) while ((int)elapsed(t_red) < 0) {} }
            exchange_wait(accp + eoff(1), (float)NFFN, PD2);
        }
        STAMP(1 + layer * 14);
        float ls, lq;
        {
            uint4 u0 = lds128(a_row + OFF_XS), u1 = lds128(a_row + OFF_XS + 16);
            float acc[4][4];
#pragma unroll
            for (int a = 0; a < 4; a++) { zero4(acc[a]); mma(acc[a], S[a * 4 + 0], u0.x, u0.y); }
            ln_partials(u0, u1, g & 1, ls, lq);
#pragma unroll
            for (int a = 0; a < 4; a++) mma(acc[a], S[a * 4 + 1], u0.z, u0.w);
#pragma unroll
            for (int a = 0; a < 4; a++) mma(acc[a], S[a * 4 + 2], u1.x, u1.y);
#pragma unroll
            for (int a = 0; a < 4; a++) mma(acc[a], S[a * 4 + 3], u1.z, u1.w);
            float e0 = (t & 2) ? ((t & 1) ? acc[3][0] : acc[2][0]) : ((t & 1) ? acc[1][0] : acc[0][0]);
            float e1 = (t & 2) ? ((t & 1) ? acc[3][3] : acc[2][3]) : ((t & 1) ? acc[1][3] : acc[0][3]);
            float q = fmaf(-ls, cs_q, e0) + e1;
            q += __shfl_xor_sync(0xffffffffu, q, 1);
            q += __shfl_xor_sync(0xffffffffu, q, 2);
            if (t == 0) sts16(a_qo + OFF_QS, pack_bf16(q, 0.f));
        }
        STAMP(2 + layer * 14);
        cta_sync();
        if (layer == 0) {
            mbar_wait(sb + OFF_BAR + (w >> 1) * BS + B_K, 0);
#pragma unroll
            for (int j = 0; j < 16; j++)
                ldsm4(Kf[j], sb + OFF_K + w * 8192 + ((j >> 2) * 16 + (mi & 1) * 8 + li) * 128 + ((((j & 3) * 2 + (mi >> 1)) ^ li) << 4));
        }
        float s0, s1, scl;
        {
            uint4 q0 = lds128(a_t32 + OFF_QS), q1 = lds128(a_t32 + OFF_QS + 16);
            float sc[4][4];
#pragma unroll
            for (int j = 0; j < 4; j++) { zero4(sc[j]); mma(sc[j], Kf[j * 4 + 0], q0.x, q0.y); }
#pragma unroll
            for (int j = 0; j < 4; j++) mma(sc[j], Kf[j * 4 + 1], q0.z, q0.w);
#pragma unroll
            for (int j = 0; j < 4; j++) mma(sc[j], Kf[j * 4 + 2], q1.x, q1.y);
#pragma unroll
            for (int j = 0; j < 4; j++) mma(sc[j], Kf[j * 4 + 3], q1.z, q1.w);
            float mean, rstd;
            ln_finish(ls, lq, mean, rstd);
            scl = rstd * (0.08838834764831845f * 1.4426950408889634f);
            s0 = (t & 2) ? ((t & 1) ? sc[3][0] : sc[2][0]) : ((t & 1) ? sc[1][0] : sc[0][0]);
            s1 = (t & 2) ? ((t & 1) ? sc[3][2] : sc[2][2]) : ((t & 1) ? sc[1][2] : sc[0][2]);
            asm volatile("st.async.weak.shared::cluster.mbarrier::complete_tx::bytes.v2.f32 [%0], {%1,%2}, [%3];"
                         ::"r"(peer_sx + (layer ? OFF_SX1 : OFF_SX0)), "f"(s0), "f"(s1), "r"(peer_bar) : "memory");
            FENCE();
            if (layer == 1) {
#pragma unroll
                for (int j = 0; j < NWO1; j++) ldsm4t(S[j], (a_wo ^ ((j & 3) << 5)) + (j >> 2) * 2048);
            }
        }
        STAMP(3 + layer * 14);
        if (layer == 0 && w < 5) {
            if (elect_one()) {
                mbar_expect(bars + B_WO, 8192);
                tma2d(wo_box, &mp.wo, w * 64, h * 128 + r * 64, bars + B_WO);
            }
            __syncwarp();
        }
        s0 *= scl; s1 *= scl;
        mbar_wait(a_bsx, layer);
        {
            float2 o2 = lds64f(a_sx + (layer ? OFF_SX1 : OFF_SX0));
            s0 = fmaf(o2.x, scl, s0);
            s1 = fmaf(o2.y, scl, s1);
            int mi_ = __float_as_int(fmaxf(fmaxf(s0, s1), -3.0e38f));
            mi_ ^= (mi_ >> 31) & 0x7fffffff;
            mi_ = __reduce_max_sync(0xffffffffu, mi_);
            mi_ ^= (mi_ >> 31) & 0x7fffffff;
            const float mw = __int_as_float(mi_);
            uint32_t pp = pack_bf16(ex2(s0 - mw), ex2(s1 - mw));
            sts16(a_pst, pp);
            sts16(a_pst + 4, pp >> 16);
            if (lane == 0) sts32f(a_qo + OFF_M, mw);
            if (layer == 1) {
                FENCE();
#pragma unroll
                for (int j = NWO1; j < NWO2; j++) ldsm4t(S[j], (a_wo ^ ((j & 3) << 5)) + (j >> 2) * 2048);
            }
        }
        STAMP(4 + layer * 14);
        cta_sync();
        float M, tot;
        float2 rem, rem2;
        {
            uint4 u0 = lds128(a_row + OFF_PS), u1 = lds128(a_row + OFF_PS + 16);
            float mg = lds32f(a_mg);
            float4 m0 = lds128f(a_sb + OFF_M), m1 = lds128f(a_sb + OFF_M + 16);
            float2 mt = lds64f(a_mt);
            if (w == 0) {
                float c[4], d[4];
                zero4(c); zero4(d);
                mma_ab(c, u0.x, u0.y, u0.z, u0.w, ONES, ONES);
                mma_ab(d, u1.x, u1.y, u1.z, u1.w, ONES, ONES);
                const float l0 = (c[1] + c[3]) + (d[1] + d[3]);
                if (t == 0) st_relaxed2(mlo + layer * NCTA * 16, mg, __uint_as_float(__float_as_uint(l0) | 0x80000000u));
                __syncwarp();
            }
            float acc[4][4];
            if (layer == 0) {
                if (lane == 0) mbar_expect(bars + B_SX, 256);
                asm volatile("{\n.reg .pred p;\nsetp.eq.u32 p, %0, 0x7fd3a5c1;\n@p nanosleep.u32 1;\n}" ::"r"(zdep) : "memory");
#pragma unroll
                for (int a = 0; a < 4; a++) {
                    if (a == 3) rem = ld_relaxed2(mlp);
                    mbar_wait(sb + OFF_BAR + a * BS + B_V, 0);
#pragma unroll
                    for (int j = 0; j < 4; j++) ldsm4t(Vf[a * 4 + j], a_gemv + OFF_V + (a * 128 + j * 16) * 128);
                    if (w13_todo && elapsed(clk0) >= TW13) { issue_w13(); w13_todo = false; }
                    zero4(acc[a]);
                    mma(acc[a], Vf[a * 4 + 0], u0.x, u0.y);
                    mma(acc[a], Vf[a * 4 + 1], u0.z, u0.w);
                    mma(acc[a], Vf[a * 4 + 2], u1.x, u1.y);
                    mma(acc[a], Vf[a * 4 + 3], u1.z, u1.w);
                }
            } else {
#pragma unroll
                for (int a = 0; a < 4; a++) { zero4(acc[a]); mma(acc[a], Vf[a * 4 + 0], u0.x, u0.y); }
#pragma unroll
                for (int a = 0; a < 4; a++) mma(acc[a], Vf[a * 4 + 1], u0.z, u0.w);
#pragma unroll
                for (int a = 0; a < 4; a++) mma(acc[a], Vf[a * 4 + 2], u1.x, u1.y);
#pragma unroll
                for (int a = 0; a < 4; a++) mma(acc[a], Vf[a * 4 + 3], u1.z, u1.w);
            }
            M = fmaxf(fmaxf(fmaxf(m0.x, m0.y), fmaxf(m0.z, m0.w)), fmaxf(fmaxf(m1.x, m1.y), fmaxf(m1.z, m1.w)));
            {
                float c[4];
                zero4(c);
                mma_ab(c, u0.x, u0.y, u0.z, u0.w, ONES, ONES);
                mma_ab(c, u1.x, u1.y, u1.z, u1.w, ONES, ONES);
                tot = (c[0] + c[2]) * ex2(mg - M);
            }
            const float f0 = ex2(mt.x - M), f1 = ex2(mt.y - M);
            float e0 = (t & 2) ? ((t & 1) ? acc[3][0] : acc[2][0]) : ((t & 1) ? acc[1][0] : acc[0][0]);
            float e1 = (t & 2) ? ((t & 1) ? acc[3][3] : acc[2][3]) : ((t & 1) ? acc[1][3] : acc[0][3]);
            float o = fmaf(f0, e0, f1 * e1);
            if (layer == 1) { FENCE(); rem = ld_relaxed2(mlp + NCTA * 16); }
            o += __shfl_xor_sync(0xffffffffu, o, 1);
            o += __shfl_xor_sync(0xffffffffu, o, 2);
            if (t == 0) sts16(a_qo + OFF_OS, pack_bf16(o, 0.f));
            if (layer == 1) {
                FENCE();
#pragma unroll
                for (int j = NWO2; j < NWO3; j++) ldsm4t(S[j], (a_wo ^ ((j & 3) << 5)) + (j >> 2) * 2048);
            }
        }
        STAMP(5 + layer * 14);
        cta_sync();
        if (layer == 0) {
            mbar_wait(bars + B_WO, 0);
#pragma unroll
            for (int j = 0; j < NWO3; j++) ldsm4t(S[j], (a_wo ^ ((j & 3) << 5)) + (j >> 2) * 2048);
        }
        {
            uint4 o0 = lds128(a_t32 + OFF_OS), o1 = lds128(a_t32 + OFF_OS + 16);
#pragma unroll
            for (int j = NWO3; j < 16; j++) ldsm4t(S[j], (a_wo ^ ((j & 3) << 5)) + (j >> 2) * 2048);
            rem2 = ld_relaxed2(mlp + layer * NCTA * 16);
            FENCE();
            float y[4][4];
#pragma unroll
            for (int j = 0; j < 4; j++) { zero4(y[j]); mma(y[j], S[j], o0.x, o0.y); }
#pragma unroll
            for (int j = 0; j < 4; j++) mma(y[j], S[4 + j], o0.z, o0.w);
#pragma unroll
            for (int j = 0; j < 4; j++) mma(y[j], S[8 + j], o1.x, o1.y);
#pragma unroll
            for (int j = 0; j < 4; j++) mma(y[j], S[12 + j], o1.z, o1.w);
            FENCE();
            STAMP(6 + layer * 14);
            if (!__all_sync(0xffffffffu, __float_as_uint(rem.y) != 0u)) {
                rem = rem2;
                int n = 0;
                while (!__all_sync(0xffffffffu, __float_as_uint(rem.y) != 0u) && ++n < SPIN_LIMIT) rem = ld_relaxed2(mlp + layer * NCTA * 16);
            }
            tot = fmaf(-rem.y, ex2(rem.x - M), tot);
            tot += __shfl_xor_sync(0xffffffffu, tot, 4);
            tot += __shfl_xor_sync(0xffffffffu, tot, 8);
            tot += __shfl_xor_sync(0xffffffffu, tot, 16);
            const float inv = rcp(tot);
            float v0 = (t == 0) ? y[0][0] : (t == 1) ? y[1][2] : y[3][0];
            float v1 = (t == 0) ? y[0][2] : (t == 1) ? y[2][0] : y[3][2];
            float v2 = (t == 0) ? y[1][0] : (t == 1) ? y[2][2] : 0.f;
            if (own) red4(accw + layer * eoff(2), v0 * inv, v1 * inv, v2 * inv, 1.f);
            t_red = elapsed(0);
            if (layer == 1 && w == 0 && t == 0) st_relaxed2(mlo, 0.f, 0.f);
        }
        STAMP(7 + layer * 14);

        if (ffn) {
            const uint32_t a_fst = sb + OFF_FP + ((w & 1) * 8 + g) * 32 + (w >> 1) * 8;
            const uint32_t a_frd = sb + OFF_FP + (lane & 15) * 32;
            const uint32_t a_w2 = sb + OFF_W2 + w * 2048 + ((mi >> 1) * 8 + li) * 128 + (((mi & 1) ^ li) << 4);
            const uint32_t a_xf = a_t32 + OFF_XS + (w >> 1) * 2 * VS;
            if (layer == 0) {
                while (elapsed(clk0) < TW13) {}
                if (w13_todo) issue_w13();
                if (w >= 4 && elect_one()) {
                    mbar_expect(bars + B_F, 4096);
                    tma2d(sb + OFF_W2 + (w - 4) * 4096, &mp.w2, (w - 4) * 128, b * 16, bars + B_F);
                    tma2d(sb + OFF_W2 + (w - 4) * 4096 + 2048, &mp.w2, (w - 4) * 128 + 64, b * 16, bars + B_F);
                }
                __syncwarp();
                mbar_wait(sb + OFF_BAR + (w >> 2) * 2 * BS + B_F, 0);
                mbar_wait(sb + OFF_BAR + (w >> 2) * 2 * BS + BS + B_F, 0);
            }
            {
                const uint32_t base = sb + OFF_W13 + (w >> 2) * 16384 + (mi & 1) * 8192 + (((w >> 1) & 1) * 128 + (mi >> 1) * 8 + li) * 32 + (((w & 1) ^ (li >> 2)) << 4);
#pragma unroll
                for (int j = 0; j < 8; j++) ldsm4t(S[j], base + j * 16 * 32);
            }
            if (layer == 0) {
                float c0[4], c1[4];
                zero4(c0); zero4(c1);
#pragma unroll
                for (int j = 0; j < 4; j++) { mma(c0, S[2 * j], ONES, ONES); mma(c1, S[2 * j + 1], ONES, ONES); }
                if (t == 0) asm volatile("st.shared.v2.f32 [%0], {%1,%2};" ::"r"(a_fst + (OFF_FC - OFF_FP)), "f"(c0[0] + c1[0]), "f"(c0[2] + c1[2]) : "memory");
            } else {
#pragma unroll
                for (int j = 0; j < 4; j++) ldsm4t(S[8 + j], a_w2 ^ (j << 5));
            }
            STAMP(8 + layer * 14);
            exchange_wait(accp + layer * eoff(2), (float)NCTA, layer ? PD3 : 0u);
            STAMP(9 + layer * 14);
            float mean2, rstd2;
            {
                uint4 u0 = lds128(a_row + OFF_XS), u1 = lds128(a_row + OFF_XS + 16);
                uint4 lo0 = lds128(a_xf), hi0 = lds128(a_xf + 16), lo1 = lds128(a_xf + VS), hi1 = lds128(a_xf + VS + 16);
                if (layer == 0) {
                    float4 p0 = lds128f(a_frd + (OFF_FC - OFF_FP)), p1 = lds128f(a_frd + (OFF_FC - OFF_FP) + 16);
                    cs_g = (p0.x + p0.z) + (p1.x + p1.z);
                    cs_u = (p0.y + p0.w) + (p1.y + p1.w);
                }
                FENCE();
                float s_, q_;
                ln_partials(u0, u1, g & 1, s_, q_);
                float acc[4][4];
                zero4(acc[0]); zero4(acc[1]); zero4(acc[2]); zero4(acc[3]);
                mma(acc[0], S[0], lo0.x, lo0.y); mma(acc[1], S[2], hi0.x, hi0.y); mma(acc[2], S[4], lo1.x, lo1.y); mma(acc[3], S[6], hi1.x, hi1.y);
                mma(acc[0], S[1], lo0.z, lo0.w); mma(acc[1], S[3], hi0.z, hi0.w); mma(acc[2], S[5], lo1.z, lo1.w); mma(acc[3], S[7], hi1.z, hi1.w);
                ln_finish(s_, q_, mean2, rstd2);
                if (t == 0) asm volatile("st.shared.v2.f32 [%0], {%1,%2};" ::"r"(a_fst), "f"((acc[0][0] + acc[1][0]) + (acc[2][0] + acc[3][0])),
                                         "f"((acc[0][2] + acc[1][2]) + (acc[2][2] + acc[3][2])) : "memory");
            }
            STAMP(10 + layer * 14);
            cta_sync();
            {
                float4 p0 = lds128f(a_frd), p1 = lds128f(a_frd + 16);
                if (layer == 0) {
                    mbar_wait(sb + OFF_BAR + (4 + (w >> 1)) * BS + B_F, 0);
#pragma unroll
                    for (int j = 0; j < 4; j++) ldsm4t(S[8 + j], a_w2 ^ (j << 5));
                }
                float gate = rstd2 * (fmaf(-mean2, cs_g, p0.x + p0.z) + (p1.x + p1.z));
                float up = rstd2 * (fmaf(-mean2, cs_u, p0.y + p0.w) + (p1.y + p1.w));
                float hv = gate * up * rcp(1.f + ex2(-1.4426950408889634f * gate));
                float h0 = __shfl_sync(0xffffffffu, hv, 2 * t), h1 = __shfl_sync(0xffffffffu, hv, 2 * t + 1);
                float h2 = __shfl_sync(0xffffffffu, hv, 2 * t + 8), h3 = __shfl_sync(0xffffffffu, hv, 2 * t + 9);
                const uint32_t b0 = pack_bf16(h0, h1), b1 = pack_bf16(h2, h3);
                float y[4][4];
#pragma unroll
                for (int j = 0; j < 4; j++) {
                    zero4(y[j]);
                    mma(y[j], S[8 + j], b0, b1);
                }
                float v0 = (t == 0) ? y[0][0] : (t == 1) ? y[1][2] : y[3][0];
                float v1 = (t == 0) ? y[0][2] : (t == 1) ? y[2][0] : y[3][2];
                float v2 = (t == 0) ? y[1][0] : (t == 1) ? y[2][2] : 0.f;
                STAMP(11 + layer * 14);
                if (layer == 0) {
                    if (own) red4(accw + eoff(1), v0, v1, v2, 1.f);
                    t_red = elapsed(0);
                } else if (own) {
                    float4 old = atom4(accp + eoff(3) + (g & 1) * 208, v0, v1, v2, 1.f);
                    if (b < 2) st_relaxed4(accw + eoff(0), 0.f, 0.f, 0.f, 0.f);
                    if (old.w == (float)(NFFN - 1)) {
                        const int c = 64 * w + 24 * t + g;
                        out[c] = __float2bfloat16(xo[0] + (old.x + v0));
                        out[c + 8] = __float2bfloat16(xo[1] + (old.y + v1));
                        if (t < 2) out[c + 16] = __float2bfloat16(xo[2] + (old.z + v2));
                    }
                }
            }
            STAMP(12 + layer * 14);
        }
    }
}

typedef CUresult (*EncodeFn)(CUtensorMap*, CUtensorMapDataType, cuuint32_t, void*, const cuuint64_t*, const cuuint64_t*,
                             const cuuint32_t*, const cuuint32_t*, CUtensorMapInterleave, CUtensorMapSwizzle,
                             CUtensorMapL2promotion, CUtensorMapFloatOOBfill);

void make_map(EncodeFn enc, CUtensorMap* m, const void* p, uint64_t cols, uint64_t rows, uint32_t bc, uint32_t br) {
    cuuint64_t gd[2] = {cols, rows};
    cuuint64_t gs[1] = {cols * 2};
    cuuint32_t bd[2] = {bc, br};
    cuuint32_t es[2] = {1, 1};
    enc(m, CU_TENSOR_MAP_DATA_TYPE_BFLOAT16, 2, const_cast<void*>(p), gd, gs, bd, es, CU_TENSOR_MAP_INTERLEAVE_NONE,
        bc == 64 ? CU_TENSOR_MAP_SWIZZLE_128B : CU_TENSOR_MAP_SWIZZLE_32B, CU_TENSOR_MAP_L2_PROMOTION_NONE,
        CU_TENSOR_MAP_FLOAT_OOB_FILL_NONE);
}

}

extern "C" void kernel_launch(void* const* d_in, const int* in_sizes, int n_in, void* d_out, int out_size) {
    (void)in_sizes; (void)n_in; (void)out_size;
    static EncodeFn enc = nullptr;
    static unsigned char* acc = nullptr;
    static MlRow* ml = nullptr;
    if (!enc) {
        void* p = nullptr;
        cudaGetSymbolAddress(&p, g_acc_raw);
        acc = reinterpret_cast<unsigned char*>((reinterpret_cast<uintptr_t>(p) + 32767) & ~(uintptr_t)32767);
        cudaGetSymbolAddress(&p, g_ml_buf);
        ml = reinterpret_cast<MlRow*>(p);
        cudaDriverEntryPointQueryResult qr;
        void* fn = nullptr;
        cudaGetDriverEntryPoint("cuTensorMapEncodeTiled", &fn, cudaEnableDefault, &qr);
        enc = (EncodeFn)fn;
        cudaFuncSetAttribute(fused_kernel, cudaFuncAttributeMaxDynamicSharedMemorySize, (int)SMEM_BYTES);
    }
    Maps mp;
    make_map(enc, &mp.wq, d_in[3], 4096, 512, 64, 256);
    make_map(enc, &mp.k, d_in[1], 128, 32 * 4096, 64, 128);
    make_map(enc, &mp.v, d_in[2], 128, 32 * 4096, 64, 128);
    make_map(enc, &mp.wo, d_in[4], 512, 4096, 64, 64);
    make_map(enc, &mp.w1, d_in[6], 1376, 512, 16, 256);
    make_map(enc, &mp.w3, d_in[7], 1376, 512, 16, 256);
    make_map(enc, &mp.w2, d_in[8], 512, 1376, 64, 16);
    fused_kernel<<<NCTA, NTHR, SMEM_BYTES>>>((const __nv_bfloat16*)d_in[0], (__nv_bfloat16*)d_out, acc, ml, mp);
}
```

```cpp
#include <cuda_runtime.h>
#include <cuda_bf16.h>
#include <cuda.h>
#include <stdint.h>

namespace {

constexpr int NCTA = 128;
constexpr int NTHR = 256;
constexpr int NFFN = 86;
#define TWO 11000u
#define NWO1 8
#define NWO2 10
#define NWO3 12
#define PD2 600u
#define PD3 600u
#define PDN 900u
#define KA 1
#define VA 2
#define KB 1
#define RA 2
#define TW2 TW13
#define TW13 13500u
constexpr int SPIN_LIMIT = 1 << 22;

constexpr uint32_t OFF_WQ = 0;
constexpr uint32_t OFF_K = 65536;
constexpr uint32_t OFF_W13 = OFF_K + 5 * 8192;
constexpr uint32_t OFF_SX0 = OFF_K + 65536;
constexpr uint32_t OFF_WO5 = OFF_SX0 + 8192;
constexpr uint32_t OFF_V = OFF_WO5 + 24576;
constexpr uint32_t OFF_W2 = OFF_V;
constexpr uint32_t OFF_SX1 = OFF_V + 16384;
constexpr uint32_t OFF_FP = OFF_SX1 + 2048;
constexpr uint32_t OFF_FC = OFF_FP + 512;
constexpr uint32_t VS = 144;
constexpr uint32_t OFF_XS = OFF_V + 65536;
constexpr uint32_t OFF_PS = OFF_XS + 1152;
constexpr uint32_t OFF_QS = OFF_PS + 1152;
constexpr uint32_t OFF_OS = OFF_QS + 128;
constexpr uint32_t OFF_M = OFF_OS + 128;
constexpr uint32_t OFF_SQ = OFF_M + 32;
constexpr uint32_t OFF_BAR = OFF_SQ + 32;
constexpr uint32_t BS = 48;
constexpr uint32_t B_WQ = 0, B_K = 8, B_V = 16, B_WO = 24, B_F = 32, B_SX = 40;
constexpr uint32_t SMEM_BYTES = OFF_BAR + 8 * BS;
static_assert(SMEM_BYTES <= 232448, "smem");

struct Maps { CUtensorMap wq, k, v, wo, w1, w3, w2; };

typedef float2 MlRow[NCTA][16];
__device__ __align__(128) unsigned char g_acc_raw[65536];
__device__ __align__(128) float2 g_ml_buf[2][NCTA][16];
#define PROF_PARAM
#define STAMP(k) do {} while (0)

__device__ __forceinline__ void mbar_init(uint32_t a, int c) {
    asm volatile("mbarrier.init.shared::cta.b64 [%0], %1;" ::"r"(a), "r"(c) : "memory");
}
__device__ __forceinline__ void mbar_expect(uint32_t a, uint32_t bytes) {
    asm volatile("mbarrier.arrive.expect_tx.shared::cta.b64 _, [%0], %1;" ::"r"(a), "r"(bytes) : "memory");
}
__device__ __forceinline__ void mbar_wait(uint32_t a, uint32_t parity) {
    uint32_t ok;
    int n = 0;
    do {
        asm volatile("{\n.reg .pred p;\nmbarrier.try_wait.parity.shared::cta.b64 p, [%1], %2;\nselp.u32 %0, 1, 0, p;\n}"
                     : "=r"(ok) : "r"(a), "r"(parity) : "memory");
    } while (!ok && ++n < SPIN_LIMIT);
}
__device__ __forceinline__ void mbar_wait_cluster(uint32_t a, uint32_t parity) {
    uint32_t ok;
    int n = 0;
    do {
        asm volatile("{\n.reg .pred p;\nmbarrier.try_wait.parity.acquire.cluster.shared::cta.b64 p, [%1], %2;\nselp.u32 %0, 1, 0, p;\n}"
                     : "=r"(ok) : "r"(a), "r"(parity) : "memory");
    } while (!ok && ++n < SPIN_LIMIT);
}
__device__ __forceinline__ void tma2d(uint32_t dst, const CUtensorMap* m, int c0, int c1, uint32_t bar) {
    asm volatile("cp.async.bulk.tensor.2d.shared::cluster.global.mbarrier::complete_tx::bytes [%0], [%1, {%3, %4}], [%2];"
                 ::"r"(dst), "l"(m), "r"(bar), "r"(c0), "r"(c1) : "memory");
}
__device__ __forceinline__ void ldsm4(uint32_t* r, uint32_t a) {
    asm volatile("ldmatrix.sync.aligned.m8n8.x4.shared.b16 {%0,%1,%2,%3}, [%4];"
                 : "=r"(r[0]), "=r"(r[1]), "=r"(r[2]), "=r"(r[3]) : "r"(a) : "memory");
}
__device__ __forceinline__ void ldsm4t(uint32_t* r, uint32_t a) {
    asm volatile("ldmatrix.sync.aligned.m8n8.x4.trans.shared.b16 {%0,%1,%2,%3}, [%4];"
                 : "=r"(r[0]), "=r"(r[1]), "=r"(r[2]), "=r"(r[3]) : "r"(a) : "memory");
}
__device__ __forceinline__ void mma(float* c, const uint32_t* a, uint32_t b0, uint32_t b1) {
    asm("mma.sync.aligned.m16n8k16.row.col.f32.bf16.bf16.f32 {%0,%1,%2,%3},{%4,%5,%6,%7},{%8,%9},{%0,%1,%2,%3};"
        : "+f"(c[0]), "+f"(c[1]), "+f"(c[2]), "+f"(c[3])
        : "r"(a[0]), "r"(a[1]), "r"(a[2]), "r"(a[3]), "r"(b0), "r"(b1));
}
__device__ __forceinline__ uint4 lds128(uint32_t a) {
    uint4 v;
    asm volatile("ld.shared.v4.u32 {%0,%1,%2,%3}, [%4];" : "=r"(v.x), "=r"(v.y), "=r"(v.z), "=r"(v.w) : "r"(a) : "memory");
    return v;
}
__device__ __forceinline__ float4 lds128f(uint32_t a) {
    float4 v;
    asm volatile("ld.shared.v4.f32 {%0,%1,%2,%3}, [%4];" : "=f"(v.x), "=f"(v.y), "=f"(v.z), "=f"(v.w) : "r"(a) : "memory");
    return v;
}
__device__ __forceinline__ float2 lds64f(uint32_t a) {
    float2 v;
    asm volatile("ld.shared.v2.f32 {%0,%1}, [%2];" : "=f"(v.x), "=f"(v.y) : "r"(a) : "memory");
    return v;
}
__device__ __forceinline__ float lds32f(uint32_t a) {
    float v;
    asm volatile("ld.shared.f32 %0, [%1];" : "=f"(v) : "r"(a) : "memory");
    return v;
}
__device__ __forceinline__ void sts16(uint32_t a, uint32_t v) {
    asm volatile("st.shared.u16 [%0], %1;" ::"r"(a), "h"((unsigned short)v) : "memory");
}
__device__ __forceinline__ void sts32f(uint32_t a, float v) {
    asm volatile("st.shared.f32 [%0], %1;" ::"r"(a), "f"(v) : "memory");
}
__device__ __forceinline__ void sts128f(uint32_t a, float x, float y, float z, float w) {
    asm volatile("st.shared.v4.f32 [%0], {%1,%2,%3,%4};" ::"r"(a), "f"(x), "f"(y), "f"(z), "f"(w) : "memory");
}
__device__ __forceinline__ void cta_sync() { asm volatile("bar.sync 0;" ::: "memory"); }
__device__ __forceinline__ float ex2(float x) {
    float y;
    asm("ex2.approx.ftz.f32 %0, %1;" : "=f"(y) : "f"(x));
    return y;
}
__device__ __forceinline__ float rcp(float x) {
    float y;
    asm("rcp.approx.ftz.f32 %0, %1;" : "=f"(y) : "f"(x));
    return y;
}
__device__ __forceinline__ uint32_t pack_bf16(float lo, float hi) {
    uint32_t r;
    asm("cvt.rn.bf16x2.f32 %0, %1, %2;" : "=r"(r) : "f"(hi), "f"(lo));
    return r;
}
__device__ __forceinline__ float bf16r(float x) { return __uint_as_float(pack_bf16(0.f, x) & 0xffff0000u); }
__device__ __forceinline__ float4 ld_relaxed4(const void* p) {
    float4 v;
    asm volatile("ld.relaxed.gpu.global.v4.f32 {%0,%1,%2,%3}, [%4];" : "=f"(v.x), "=f"(v.y), "=f"(v.z), "=f"(v.w) : "l"(p) : "memory");
    return v;
}
__device__ __forceinline__ float2 ld_relaxed2(const void* p) {
    float2 v;
    asm volatile("ld.relaxed.gpu.global.v2.f32 {%0,%1}, [%2];" : "=f"(v.x), "=f"(v.y) : "l"(p) : "memory");
    return v;
}
__device__ __forceinline__ void st_relaxed2(void* p, float x, float y) {
    asm volatile("st.relaxed.gpu.global.v2.f32 [%0], {%1,%2};" ::"l"(p), "f"(x), "f"(y) : "memory");
}
__device__ __forceinline__ void st_relaxed4(void* p, float x, float y, float z, float w) {
    asm volatile("st.relaxed.gpu.global.v4.f32 [%0], {%1,%2,%3,%4};" ::"l"(p), "f"(x), "f"(y), "f"(z), "f"(w) : "memory");
}
__device__ __forceinline__ void red4(void* p, float x, float y, float z, float w) {
    asm volatile("red.relaxed.gpu.global.add.v4.f32 [%0], {%1,%2,%3,%4};" ::"l"(p), "f"(x), "f"(y), "f"(z), "f"(w) : "memory");
}
__device__ __forceinline__ float4 atom4(void* p, float x, float y, float z, float w) {
    float4 v;
    asm volatile("atom.relaxed.gpu.global.add.v4.f32 {%0,%1,%2,%3}, [%4], {%5,%6,%7,%8};"
                 : "=f"(v.x), "=f"(v.y), "=f"(v.z), "=f"(v.w) : "l"(p), "f"(x), "f"(y), "f"(z), "f"(w) : "memory");
    return v;
}
__device__ __forceinline__ constexpr uint32_t eoff(int e) { return (uint32_t)((e & 1) * 128 + (e >> 1) * 512); }

constexpr uint32_t ONES = 0x3F803F80u;

__device__ __forceinline__ void mma_ab(float* c, uint32_t a0, uint32_t a1, uint32_t a2, uint32_t a3, uint32_t b0, uint32_t b1) {
    asm("mma.sync.aligned.m16n8k16.row.col.f32.bf16.bf16.f32 {%0,%1,%2,%3},{%4,%5,%6,%7},{%8,%9},{%0,%1,%2,%3};"
        : "+f"(c[0]), "+f"(c[1]), "+f"(c[2]), "+f"(c[3])
        : "r"(a0), "r"(a1), "r"(a2), "r"(a3), "r"(b0), "r"(b1));
}
__device__ __forceinline__ bool elect_one() {
    uint32_t p;
    asm volatile("{\n.reg .pred p;\nelect.sync _|p, 0xffffffff;\nselp.u32 %0, 1, 0, p;\n}" : "=r"(p));
    return p;
}
__device__ __forceinline__ float rsq(float x) {
    float y;
    asm("rsqrt.approx.ftz.f32 %0, %1;" : "=f"(y) : "f"(x));
    return y;
}
__device__ __forceinline__ uint32_t elapsed(uint32_t c0) {
    uint32_t c;
    asm volatile("mov.u32 %0, %%clock;" : "=r"(c) :: "memory");
    return __shfl_sync(0xffffffffu, c, 0) - c0 ;
}
__device__ __forceinline__ void zero4(float* c) { c[0] = c[1] = c[2] = c[3] = 0.f; }
__device__ __forceinline__ uint32_t pin(uint32_t v, int lane) { return __shfl_sync(0xffffffffu, v, lane); }

__device__ __forceinline__ void ln_partials(const uint4& u0, const uint4& u1, bool godd, float& s, float& q) {
    float c[4], d[4];
    zero4(c); zero4(d);
    mma_ab(c, u0.x, ONES, u0.y, ONES, u0.x, u0.y);
    mma_ab(d, u1.x, ONES, u1.y, ONES, u1.x, u1.y);
    mma_ab(c, u0.z, ONES, u0.w, ONES, u0.z, u0.w);
    mma_ab(d, u1.z, ONES, u1.w, ONES, u1.z, u1.w);
    s = (c[2] + d[2]) + (c[3] + d[3]);
    q = godd ? c[1] + d[1] : c[0] + d[0];
}
__device__ __forceinline__ void ln_finish(float s, float q, float& mean, float& rstd) {
    q += __shfl_xor_sync(0xffffffffu, q, 4);
    s += __shfl_xor_sync(0xffffffffu, s, 1);
    q += __shfl_xor_sync(0xffffffffu, q, 9);
    s += __shfl_xor_sync(0xffffffffu, s, 2);
    q += __shfl_xor_sync(0xffffffffu, q, 18);
    mean = s * (1.f / 512.f);
    q = __shfl_sync(0xffffffffu, q, 0);
    rstd = rsq(fmaxf(fmaf(-mean, mean, q * (1.f / 512.f)), 0.f) + 1e-5f);
}

__device__ __forceinline__ bool cta_sync_and(bool p) {
    uint32_t r;
    asm volatile("{\n.reg .pred p, q;\nsetp.ne.u32 p, %1, 0;\nbar.red.and.pred q, 0, p;\nselp.u32 %0, 1, 0, q;\n}" : "=r"(r) : "r"((uint32_t)p) : "memory");
    return r;
}
#define FENCE() __syncwarp()

__global__ void __cluster_dims__(2, 1, 1) __launch_bounds__(NTHR, 1)
fused_kernel(const __nv_bfloat16* __restrict__ x_in, __nv_bfloat16* __restrict__ out, unsigned char* const acc_base, MlRow* const g_ml,
             PROF_PARAM const __grid_constant__ Maps mp) {
    extern __shared__ __align__(1024) unsigned char smem[];
    const uint32_t sb = (uint32_t)__cvta_generic_to_shared(smem);
    const int tid = threadIdx.x;
    const int b = blockIdx.x, r = b & 1, pr = (b >> 1) & 1, h = b >> 2;
    unsigned clk0;
    asm volatile("mov.u32 %0, %%clock;" : "=r"(clk0) :: "memory");
    if (tid == 0) {
        mbar_init(sb + OFF_BAR + B_WQ, 1);
        asm volatile("fence.mbarrier_init.release.cluster;" ::: "memory");
        mbar_expect(sb + OFF_BAR + B_WQ, 65536 + 1024);
        asm volatile("cp.async.bulk.shared::cluster.global.mbarrier::complete_tx::bytes [%0], [%1], 1024, [%2];"
                     ::"r"(sb + OFF_PS), "l"(x_in), "r"(sb + OFF_BAR + B_WQ) : "memory");
        tma2d(sb + OFF_WQ, &mp.wq, h * 128 + r * 64, 0, sb + OFF_BAR + B_WQ);
        tma2d(sb + OFF_WQ + 32768, &mp.wq, h * 128 + r * 64, 256, sb + OFF_BAR + B_WQ);
        const int kr = h * 4096 + 3072 + pr * 512;
#pragma unroll
        for (int i = 0; i < 4; i++) { mbar_init(sb + OFF_BAR + i * BS + B_K, 1); mbar_init(sb + OFF_BAR + i * BS + B_V, 1); }
        asm volatile("fence.mbarrier_init.release.cluster;" ::: "memory");
#pragma unroll
        for (int i = 0; i < 4; i++) {
            mbar_expect(sb + OFF_BAR + i * BS + B_K, 16384);
            tma2d(sb + OFF_K + i * 16384, &mp.k, r * 64, kr + i * 128, sb + OFF_BAR + i * BS + B_K);
        }
#pragma unroll
        for (int i = 0; i < (KA == 0 ? 4 : 0); i++) {
            mbar_expect(sb + OFF_BAR + i * BS + B_V, 16384);
            tma2d(sb + OFF_V + i * 16384, &mp.v, r * 64, kr + i * 128, sb + OFF_BAR + i * BS + B_V);
        }
    }
    clk0 = __shfl_sync(0xffffffffu, clk0, 0);
    const int w = __shfl_sync(0xffffffffu, tid >> 5, 0), lane = tid & 31, g = lane >> 2, t = lane & 3;
    const bool ffn = b < NFFN;
    const uint32_t bars = sb + OFF_BAR + w * BS;
    if (elect_one()) {
        if (w >= 1 && w < 7) asm volatile("prefetch.tensormap [%0];" ::"l"(&mp.wq + w) : "memory");
        mbar_init(bars + B_WO, 1); mbar_init(bars + B_F, 1); mbar_init(bars + B_SX, 1);
        asm volatile("fence.mbarrier_init.release.cluster;" ::: "memory");
        mbar_expect(bars + B_SX, 256);
    }
    __syncwarp();
    STAMP(13);
    asm volatile("barrier.cluster.arrive.relaxed.aligned;" ::: "memory");

    unsigned char* const accp = acc_base + pin(w * 4096 + (g >> 1) * 1024 + ((g & 1) * 3 + (t < 3 ? t : 2)) * 16, lane);
    unsigned char* const accw = accp + r * 256;
    const bool own = t < 3;
    uint32_t zdep = 0;
    {
        const int z = tid - 32;
        unsigned char* zp;
        if (z < 16) zp = reinterpret_cast<unsigned char*>(&g_ml[1][b][0]) + z * 4;
        else {
            const int i = b * 48 + (z - 16), e = 1 + (i >> 11), u = (i >> 5) & 63;
            zp = acc_base + (u >> 3) * 4096 + (u & 1) * 256 + ((u >> 1) & 3) * 1024 + (e & 1) * 128 + (e >> 1) * 512 + (i & 31) * 4;
        }
        asm volatile("{\n.reg .pred p;\nsetp.lt.u32 p, %2, 64;\n@p atom.relaxed.gpu.global.exch.b32 %0, [%1], 0;\n}"
                     : "+r"(zdep) : "l"(zp), "r"(z) : "memory");
    }

    const int mi = lane >> 3, li = lane & 7;
    const uint32_t wo_box = sb + (w < 5 ? OFF_K + w * 8192 : OFF_WO5 + (w - 5) * 8192);
    const uint32_t a_gemv = pin(sb + ((mi & 1) * 64 + (mi >> 1) * 8 + li) * 128 + ((w ^ li) << 4), lane);
    const uint32_t a_wo = pin(wo_box + ((mi >> 1) * 8 + li) * 128 + (((mi & 1) ^ li) << 4), lane);
    const uint32_t a_xst = pin(sb + OFF_XS + w * VS + (g >> 1) * 32 + (g & 1) * 2 + t * 12, lane);
    const uint32_t a_pst = pin(sb + OFF_PS + w * VS + (g >> 1) * 32 + (g & 1) * 2 + t * 8, lane);
    const uint32_t a_row = pin(sb + g * VS + t * 32, lane);
    const uint32_t a_qo = pin(sb + (g >> 1) * 32 + w * 4 + (g & 1) * 2, lane);
    const uint32_t a_t32 = pin(sb + t * 32, lane);
    const uint32_t a_sx = pin(sb + tid * 8, lane);
    uint32_t peer_sx, peer_bar;
    asm volatile("mapa.shared::cluster.u32 %0, %1, %2;" : "=r"(peer_sx) : "r"(a_sx), "r"(r ^ 1));
    asm volatile("mapa.shared::cluster.u32 %0, %1, %2;" : "=r"(peer_bar) : "r"(bars + B_SX), "r"(r ^ 1));
    float2* const mlp = &g_ml[0][b ^ 2][0] + pin(g, lane);
    float2* const mlo = &g_ml[0][0][0] + pin(b * 16 + g, lane);
    const uint32_t a_mg = pin(sb + OFF_M + g * 4, lane), a_mt = pin(sb + OFF_M + t * 8, lane), a_sb = pin(sb, lane), a_bsx = pin(bars + B_SX, lane);

    auto issue_v = [&](int i) {
        if (elect_one()) {
            mbar_expect(sb + OFF_BAR + i * BS + B_V, 16384);
            tma2d(sb + OFF_V + i * 16384, &mp.v, r * 64, h * 4096 + 3072 + pr * 512 + i * 128, sb + OFF_BAR + i * BS + B_V);
        }
        __syncwarp();
    };
    auto issue_wo = [&]() {
        if (elect_one()) {
            mbar_expect(bars + B_WO, 8192);
            tma2d(wo_box, &mp.wo, w * 64, h * 128 + r * 64, bars + B_WO);
        }
        __syncwarp();
    };
    bool f_todo = ffn && w < 4;
    auto issue_f = [&]() {
        if (elect_one()) {
            if (w < 4) {
                mbar_expect(bars + B_F, 8192);
                tma2d(sb + OFF_W13 + w * 8192, (w & 1) ? &mp.w3 : &mp.w1, b * 16, (w >> 1) * 256, bars + B_F);
            } else {
                mbar_expect(bars + B_F, 4096);
                tma2d(sb + OFF_W2 + (w - 4) * 4096, &mp.w2, (w - 4) * 128, b * 16, bars + B_F);
                tma2d(sb + OFF_W2 + (w - 4) * 4096 + 2048, &mp.w2, (w - 4) * 128 + 64, b * 16, bars + B_F);
            }
        }
        __syncwarp();
        f_todo = false;
    };
    auto gated_wait = [&](uint32_t bar) {
        int n = SPIN_LIMIT;
        while (true) {
            if (f_todo && elapsed(clk0) >= (w < 4 ? TW13 : TW2)) issue_f();
            uint32_t ok;
            asm volatile("{\n.reg .pred p;\nmbarrier.test_wait.parity.shared::cta.b64 p, [%1], 0;\nselp.u32 %0, 1, 0, p;\n}" : "=r"(ok) : "r"(bar) : "memory");
            if (ok || --n < 0) break;
            if (!f_todo) { mbar_wait(bar, 0); break; }
        }
    };
    uint32_t Kf[16][4], Vf[16][4], S[16][4];
    float cs_q = 0.f, cs_g = 0.f, cs_u = 0.f;
    STAMP(0);
    asm volatile("barrier.cluster.wait.acquire.aligned;" ::: "memory");
    if (KB == 0 && w >= 5) issue_wo();
    mbar_wait(sb + OFF_BAR + B_WQ, 0);
    if (KA >= 1 && w == 0) { for (int i = 0; i < VA; i++) issue_v(i); }
    STAMP(14);
    float xo[3];
#pragma unroll
    for (int i = 0; i < 3; i++) {
        uint32_t xr;
        asm volatile("ld.shared.u16 %0, [%1];" : "=r"(xr) : "r"(sb + OFF_PS + (64 * w + 8 * ((3 * t + i) & 7) + g) * 2) : "memory");
        xo[i] = __uint_as_float(xr << 16);
    }

    auto put_x = [&](const float4& v) {
        const uint32_t p01 = pack_bf16(xo[0] + v.x, xo[1] + v.y), p2 = pack_bf16(xo[2] + v.z, 0.f);
        if (own) { sts16(a_xst, p01); sts16(a_xst + 4, p01 >> 16); }
        if (t < 2) sts16(a_xst + 8, p2);
        cta_sync();
        xo[0] = __uint_as_float(p01 << 16); xo[1] = __uint_as_float(p01 & 0xffff0000u); xo[2] = __uint_as_float(p2 << 16);
    };
    uint32_t t_red = 0;
    auto exchange_wait = [&](const unsigned char* p, float target, uint32_t delay) {
        int n = SPIN_LIMIT;
        if (delay) while (elapsed(t_red) < delay) {}
        float4 v, v2;
        do { v = ld_relaxed4(p); v2 = ld_relaxed4(p + 256); } while (__any_sync(0xffffffffu, v.w + v2.w != target) && --n > 0);
        put_x(make_float4(v.x + v2.x, v.y + v2.y, v.z + v2.z, 0.f));
    };

#pragma unroll
    for (int layer = 0; layer < 2; layer++) {
#pragma unroll
        for (int j = 0; j < 16; j++) ldsm4t(S[j], a_gemv + OFF_WQ + ((j >> 2) * 128 + (j & 3) * 16) * 128);
        if (layer == 0) {
            float c0[4], c1[4];
            zero4(c0); zero4(c1);
#pragma unroll
            for (int j = 0; j < 8; j++) { mma(c0, S[2 * j], ONES, ONES); mma(c1, S[2 * j + 1], ONES, ONES); }
            cs_q = ((c0[0] + c0[3]) + (c1[0] + c1[3])) * (1.f / 512.f);
            put_x(make_float4(0.f, 0.f, 0.f, 0.f));
        } else {
            if (!ffn) { exchange_wait(accp + eoff(0), (float)NCTA, 0); t_red = elapsed(0) + PDN; if (PDN) while ((int)elapsed(t_red) < 0) {} }
            exchange_wait(accp + eoff(1), (float)NFFN, PD2);
        }
        STAMP(1 + layer * 14);
        float ls, lq;
        {
            uint4 u0 = lds128(a_row + OFF_XS), u1 = lds128(a_row + OFF_XS + 16);
            float acc[4][4];
#pragma unroll
            for (int a = 0; a < 4; a++) { zero4(acc[a]); mma(acc[a], S[a * 4 + 0], u0.x, u0.y); }
            ln_partials(u0, u1, g & 1, ls, lq);
#pragma unroll
            for (int a = 0; a < 4; a++) mma(acc[a], S[a * 4 + 1], u0.z, u0.w);
#pragma unroll
            for (int a = 0; a < 4; a++) mma(acc[a], S[a * 4 + 2], u1.x, u1.y);
#pragma unroll
            for (int a = 0; a < 4; a++) mma(acc[a], S[a * 4 + 3], u1.z, u1.w);
            float e0 = (t & 2) ? ((t & 1) ? acc[3][0] : acc[2][0]) : ((t & 1) ? acc[1][0] : acc[0][0]);
            float e1 = (t & 2) ? ((t & 1) ? acc[3][3] : acc[2][3]) : ((t & 1) ? acc[1][3] : acc[0][3]);
            float q = fmaf(-ls, cs_q, e0) + e1;
            q += __shfl_xor_sync(0xffffffffu, q, 1);
            q += __shfl_xor_sync(0xffffffffu, q, 2);
            if (t == 0) sts16(a_qo + OFF_QS, pack_bf16(q, 0.f));
        }
        STAMP(2 + layer * 14);
        cta_sync();
        if (layer == 0) {
            mbar_wait(sb + OFF_BAR + (w >> 1) * BS + B_K, 0);
            if (KA >= 1 && !(w & 1) && (w >> 1) + VA < 4) issue_v((w >> 1) + VA);
#pragma unroll
            for (int j = 0; j < 16; j++)
                ldsm4(Kf[j], sb + OFF_K + w * 8192 + ((j >> 2) * 16 + (mi & 1) * 8 + li) * 128 + ((((j & 3) * 2 + (mi >> 1)) ^ li) << 4));
        }
        float s0, s1, scl;
        {
            uint4 q0 = lds128(a_t32 + OFF_QS), q1 = lds128(a_t32 + OFF_QS + 16);
            float sc[4][4];
#pragma unroll
            for (int j = 0; j < 4; j++) { zero4(sc[j]); mma(sc[j], Kf[j * 4 + 0], q0.x, q0.y); }
#pragma unroll
            for (int j = 0; j < 4; j++) mma(sc[j], Kf[j * 4 + 1], q0.z, q0.w);
#pragma unroll
            for (int j = 0; j < 4; j++) mma(sc[j], Kf[j * 4 + 2], q1.x, q1.y);
#pragma unroll
            for (int j = 0; j < 4; j++) mma(sc[j], Kf[j * 4 + 3], q1.z, q1.w);
            float mean, rstd;
            ln_finish(ls, lq, mean, rstd);
            scl = rstd * (0.08838834764831845f * 1.4426950408889634f);
            s0 = (t & 2) ? ((t & 1) ? sc[3][0] : sc[2][0]) : ((t & 1) ? sc[1][0] : sc[0][0]);
            s1 = (t & 2) ? ((t & 1) ? sc[3][2] : sc[2][2]) : ((t & 1) ? sc[1][2] : sc[0][2]);
            asm volatile("st.async.weak.shared::cluster.mbarrier::complete_tx::bytes.v2.f32 [%0], {%1,%2}, [%3];"
                         ::"r"(peer_sx + (layer ? OFF_SX1 : OFF_SX0)), "f"(s0), "f"(s1), "r"(peer_bar) : "memory");
            FENCE();
            if (layer == 1) {
#pragma unroll
                for (int j = 0; j < NWO1; j++) ldsm4t(S[j], (a_wo ^ ((j & 3) << 5)) + (j >> 2) * 2048);
            }
        }
        STAMP(3 + layer * 14);
        if (KB == 0 && layer == 0 && w < 5) issue_wo();
        s0 *= scl; s1 *= scl;
        mbar_wait(a_bsx, layer);
        {
            float2 o2 = lds64f(a_sx + (layer ? OFF_SX1 : OFF_SX0));
            s0 = fmaf(o2.x, scl, s0);
            s1 = fmaf(o2.y, scl, s1);
            int mi_ = __float_as_int(fmaxf(fmaxf(s0, s1), -3.0e38f));
            mi_ ^= (mi_ >> 31) & 0x7fffffff;
            mi_ = __reduce_max_sync(0xffffffffu, mi_);
            mi_ ^= (mi_ >> 31) & 0x7fffffff;
            const float mw = __int_as_float(mi_);
            uint32_t pp = pack_bf16(ex2(s0 - mw), ex2(s1 - mw));
            sts16(a_pst, pp);
            sts16(a_pst + 4, pp >> 16);
            if (lane == 0) sts32f(a_qo + OFF_M, mw);
            if (layer == 1) {
                FENCE();
#pragma unroll
                for (int j = NWO1; j < NWO2; j++) ldsm4t(S[j], (a_wo ^ ((j & 3) << 5)) + (j >> 2) * 2048);
            }
        }
        STAMP(4 + layer * 14);
        cta_sync();
        float M, tot;
        float2 rem, rem2;
        {
            uint4 u0 = lds128(a_row + OFF_PS), u1 = lds128(a_row + OFF_PS + 16);
            float mg = lds32f(a_mg);
            float4 m0 = lds128f(a_sb + OFF_M), m1 = lds128f(a_sb + OFF_M + 16);
            float2 mt = lds64f(a_mt);
            if (w == 0) {
                float c[4], d[4];
                zero4(c); zero4(d);
                mma_ab(c, u0.x, u0.y, u0.z, u0.w, ONES, ONES);
                mma_ab(d, u1.x, u1.y, u1.z, u1.w, ONES, ONES);
                const float l0 = (c[1] + c[3]) + (d[1] + d[3]);
                if (t == 0) st_relaxed2(mlo + layer * NCTA * 16, mg, __uint_as_float(__float_as_uint(l0) | 0x80000000u));
                __syncwarp();
            }
            float acc[4][4];
            if (layer == 0) {
                if (lane == 0) mbar_expect(bars + B_SX, 256);
                asm volatile("{\n.reg .pred p;\nsetp.eq.u32 p, %0, 0x7fd3a5c1;\n@p nanosleep.u32 1;\n}" ::"r"(zdep) : "memory");
                if (KB == 1) issue_wo();
                rem = make_float2(0.f, 0.f);
#pragma unroll
                for (int a = 0; a < 4; a++) {
                    if (a == RA) rem = ld_relaxed2(mlp);
                    gated_wait(sb + OFF_BAR + a * BS + B_V);
                    if (KB == 2 && (w >> 2) == a) issue_wo();
#pragma unroll
                    for (int j = 0; j < 4; j++) ldsm4t(Vf[a * 4 + j], a_gemv + OFF_V + (a * 128 + j * 16) * 128);
                    zero4(acc[a]);
                    mma(acc[a], Vf[a * 4 + 0], u0.x, u0.y);
                    mma(acc[a], Vf[a * 4 + 1], u0.z, u0.w);
                    mma(acc[a], Vf[a * 4 + 2], u1.x, u1.y);
                    mma(acc[a], Vf[a * 4 + 3], u1.z, u1.w);
                }
            } else {
#pragma unroll
                for (int a = 0; a < 4; a++) { zero4(acc[a]); mma(acc[a], Vf[a * 4 + 0], u0.x, u0.y); }
#pragma unroll
                for (int a = 0; a < 4; a++) mma(acc[a], Vf[a * 4 + 1], u0.z, u0.w);
#pragma unroll
                for (int a = 0; a < 4; a++) mma(acc[a], Vf[a * 4 + 2], u1.x, u1.y);
#pragma unroll
                for (int a = 0; a < 4; a++) mma(acc[a], Vf[a * 4 + 3], u1.z, u1.w);
            }
            M = fmaxf(fmaxf(fmaxf(m0.x, m0.y), fmaxf(m0.z, m0.w)), fmaxf(fmaxf(m1.x, m1.y), fmaxf(m1.z, m1.w)));
            {
                float c[4];
                zero4(c);
                mma_ab(c, u0.x, u0.y, u0.z, u0.w, ONES, ONES);
                mma_ab(c, u1.x, u1.y, u1.z, u1.w, ONES, ONES);
                tot = (c[0] + c[2]) * ex2(mg - M);
            }
            const float f0 = ex2(mt.x - M), f1 = ex2(mt.y - M);
            float e0 = (t & 2) ? ((t & 1) ? acc[3][0] : acc[2][0]) : ((t & 1) ? acc[1][0] : acc[0][0]);
            float e1 = (t & 2) ? ((t & 1) ? acc[3][3] : acc[2][3]) : ((t & 1) ? acc[1][3] : acc[0][3]);
            float o = fmaf(f0, e0, f1 * e1);
            if (layer == 1) { FENCE(); rem = ld_relaxed2(mlp + NCTA * 16); }
            o += __shfl_xor_sync(0xffffffffu, o, 1);
            o += __shfl_xor_sync(0xffffffffu, o, 2);
            if (t == 0) sts16(a_qo + OFF_OS, pack_bf16(o, 0.f));
            if (layer == 1) {
                FENCE();
#pragma unroll
                for (int j = NWO2; j < NWO3; j++) ldsm4t(S[j], (a_wo ^ ((j & 3) << 5)) + (j >> 2) * 2048);
            }
        }
        STAMP(5 + layer * 14);
        cta_sync();
        if (layer == 0) {
            if (w >= 4) f_todo = ffn;
            gated_wait(bars + B_WO);
#pragma unroll
            for (int j = 0; j < NWO3; j++) ldsm4t(S[j], (a_wo ^ ((j & 3) << 5)) + (j >> 2) * 2048);
        }
        {
            uint4 o0 = lds128(a_t32 + OFF_OS), o1 = lds128(a_t32 + OFF_OS + 16);
#pragma unroll
            for (int j = NWO3; j < 16; j++) ldsm4t(S[j], (a_wo ^ ((j & 3) << 5)) + (j >> 2) * 2048);
            if (layer == 1) rem2 = ld_relaxed2(mlp + layer * NCTA * 16); else rem2 = rem;
            FENCE();
            float y[4][4];
#pragma unroll
            for (int j = 0; j < 4; j++) { zero4(y[j]); mma(y[j], S[j], o0.x, o0.y); }
#pragma unroll
            for (int j = 0; j < 4; j++) mma(y[j], S[4 + j], o0.z, o0.w);
#pragma unroll
            for (int j = 0; j < 4; j++) mma(y[j], S[8 + j], o1.x, o1.y);
#pragma unroll
            for (int j = 0; j < 4; j++) mma(y[j], S[12 + j], o1.z, o1.w);
            FENCE();
            STAMP(6 + layer * 14);
            if (!__all_sync(0xffffffffu, __float_as_uint(rem.y) != 0u)) {
                rem = rem2;
                int n = 0;
                while (!__all_sync(0xffffffffu, __float_as_uint(rem.y) != 0u) && ++n < SPIN_LIMIT) rem = ld_relaxed2(mlp + layer * NCTA * 16);
            }
            tot = fmaf(-rem.y, ex2(rem.x - M), tot);
            tot += __shfl_xor_sync(0xffffffffu, tot, 4);
            tot += __shfl_xor_sync(0xffffffffu, tot, 8);
            tot += __shfl_xor_sync(0xffffffffu, tot, 16);
            const float inv = rcp(tot);
            float v0 = (t == 0) ? y[0][0] : (t == 1) ? y[1][2] : y[3][0];
            float v1 = (t == 0) ? y[0][2] : (t == 1) ? y[2][0] : y[3][2];
            float v2 = (t == 0) ? y[1][0] : (t == 1) ? y[2][2] : 0.f;
            if (own) red4(accw + layer * eoff(2), v0 * inv, v1 * inv, v2 * inv, 1.f);
            t_red = elapsed(0);
            if (layer == 1 && w == 0 && t == 0) st_relaxed2(mlo, 0.f, 0.f);
        }
        STAMP(7 + layer * 14);

        if (ffn) {
            const uint32_t a_fst = sb + OFF_FP + ((w & 1) * 8 + g) * 32 + (w >> 1) * 8;
            const uint32_t a_frd = sb + OFF_FP + (lane & 15) * 32;
            const uint32_t a_w2 = sb + OFF_W2 + w * 2048 + ((mi >> 1) * 8 + li) * 128 + (((mi & 1) ^ li) << 4);
            const uint32_t a_xf = a_t32 + OFF_XS + (w >> 1) * 2 * VS;
            if (layer == 0) {
                if (f_todo) {
                    while (elapsed(clk0) < (w < 4 ? TW13 : TW2)) {}
                    issue_f();
                }
                mbar_wait(sb + OFF_BAR + (w >> 2) * 2 * BS + B_F, 0);
                mbar_wait(sb + OFF_BAR + (w >> 2) * 2 * BS + BS + B_F, 0);
            }
            {
                const uint32_t base = sb + OFF_W13 + (w >> 2) * 16384 + (mi & 1) * 8192 + (((w >> 1) & 1) * 128 + (mi >> 1) * 8 + li) * 32 + (((w & 1) ^ (li >> 2)) << 4);
#pragma unroll
                for (int j = 0; j < 8; j++) ldsm4t(S[j], base + j * 16 * 32);
            }
            if (layer == 0) {
                float c0[4], c1[4];
                zero4(c0); zero4(c1);
#pragma unroll
                for (int j = 0; j < 4; j++) { mma(c0, S[2 * j], ONES, ONES); mma(c1, S[2 * j + 1], ONES, ONES); }
                if (t == 0) asm volatile("st.shared.v2.f32 [%0], {%1,%2};" ::"r"(a_fst + (OFF_FC - OFF_FP)), "f"(c0[0] + c1[0]), "f"(c0[2] + c1[2]) : "memory");
            } else {
#pragma unroll
                for (int j = 0; j < 4; j++) ldsm4t(S[8 + j], a_w2 ^ (j << 5));
            }
            STAMP(8 + layer * 14);
            exchange_wait(accp + layer * eoff(2), (float)NCTA, layer ? PD3 : 0u);
            STAMP(9 + layer * 14);
            float mean2, rstd2;
            {
                uint4 u0 = lds128(a_row + OFF_XS), u1 = lds128(a_row + OFF_XS + 16);
                uint4 lo0 = lds128(a_xf), hi0 = lds128(a_xf + 16), lo1 = lds128(a_xf + VS), hi1 = lds128(a_xf + VS + 16);
                if (layer == 0) {
                    float4 p0 = lds128f(a_frd + (OFF_FC - OFF_FP)), p1 = lds128f(a_frd + (OFF_FC - OFF_FP) + 16);
                    cs_g = (p0.x + p0.z) + (p1.x + p1.z);
                    cs_u = (p0.y + p0.w) + (p1.y + p1.w);
                }
                FENCE();
                float s_, q_;
                ln_partials(u0, u1, g & 1, s_, q_);
                float acc[4][4];
                zero4(acc[0]); zero4(acc[1]); zero4(acc[2]); zero4(acc[3]);
                mma(acc[0], S[0], lo0.x, lo0.y); mma(acc[1], S[2], hi0.x, hi0.y); mma(acc[2], S[4], lo1.x, lo1.y); mma(acc[3], S[6], hi1.x, hi1.y);
                mma(acc[0], S[1], lo0.z, lo0.w); mma(acc[1], S[3], hi0.z, hi0.w); mma(acc[2], S[5], lo1.z, lo1.w); mma(acc[3], S[7], hi1.z, hi1.w);
                ln_finish(s_, q_, mean2, rstd2);
                if (t == 0) asm volatile("st.shared.v2.f32 [%0], {%1,%2};" ::"r"(a_fst), "f"((acc[0][0] + acc[1][0]) + (acc[2][0] + acc[3][0])),
                                         "f"((acc[0][2] + acc[1][2]) + (acc[2][2] + acc[3][2])) : "memory");
            }
            STAMP(10 + layer * 14);
            cta_sync();
            {
                float4 p0 = lds128f(a_frd), p1 = lds128f(a_frd + 16);
                if (layer == 0) {
                    mbar_wait(sb + OFF_BAR + (4 + (w >> 1)) * BS + B_F, 0);
#pragma unroll
                    for (int j = 0; j < 4; j++) ldsm4t(S[8 + j], a_w2 ^ (j << 5));
                }
                float gate = rstd2 * (fmaf(-mean2, cs_g, p0.x + p0.z) + (p1.x + p1.z));
                float up = rstd2 * (fmaf(-mean2, cs_u, p0.y + p0.w) + (p1.y + p1.w));
                float hv = gate * up * rcp(1.f + ex2(-1.4426950408889634f * gate));
                float h0 = __shfl_sync(0xffffffffu, hv, 2 * t), h1 = __shfl_sync(0xffffffffu, hv, 2 * t + 1);
                float h2 = __shfl_sync(0xffffffffu, hv, 2 * t + 8), h3 = __shfl_sync(0xffffffffu, hv, 2 * t + 9);
                const uint32_t b0 = pack_bf16(h0, h1), b1 = pack_bf16(h2, h3);
                float y[4][4];
#pragma unroll
                for (int j = 0; j < 4; j++) {
                    zero4(y[j]);
                    mma(y[j], S[8 + j], b0, b1);
                }
                float v0 = (t == 0) ? y[0][0] : (t == 1) ? y[1][2] : y[3][0];
                float v1 = (t == 0) ? y[0][2] : (t == 1) ? y[2][0] : y[3][2];
                float v2 = (t == 0) ? y[1][0] : (t == 1) ? y[2][2] : 0.f;
                STAMP(11 + layer * 14);
                if (layer == 0) {
                    if (own) red4(accw + eoff(1), v0, v1, v2, 1.f);
                    t_red = elapsed(0);
                } else if (own) {
                    float4 old = atom4(accp + eoff(3) + (g & 1) * 208, v0, v1, v2, 1.f);
                    if (b < 2) st_relaxed4(accw + eoff(0), 0.f, 0.f, 0.f, 0.f);
                    if (old.w == (float)(NFFN - 1)) {
                        const int c = 64 * w + 24 * t + g;
                        out[c] = __float2bfloat16(xo[0] + (old.x + v0));
                        out[c + 8] = __float2bfloat16(xo[1] + (old.y + v1));
                        if (t < 2) out[c + 16] = __float2bfloat16(xo[2] + (old.z + v2));
                    }
                }
            }
            STAMP(12 + layer * 14);
        }
    }
}

typedef CUresult (*EncodeFn)(CUtensorMap*, CUtensorMapDataType, cuuint32_t, void*, const cuuint64_t*, const cuuint64_t*,
                             const cuuint32_t*, const cuuint32_t*, CUtensorMapInterleave, CUtensorMapSwizzle,
                             CUtensorMapL2promotion, CUtensorMapFloatOOBfill);

void make_map(EncodeFn enc, CUtensorMap* m, const void* p, uint64_t cols, uint64_t rows, uint32_t bc, uint32_t br) {
    cuuint64_t gd[2] = {cols, rows};
    cuuint64_t gs[1] = {cols * 2};
    cuuint32_t bd[2] = {bc, br};
    cuuint32_t es[2] = {1, 1};
    enc(m, CU_TENSOR_MAP_DATA_TYPE_BFLOAT16, 2, const_cast<void*>(p), gd, gs, bd, es, CU_TENSOR_MAP_INTERLEAVE_NONE,
        bc == 64 ? CU_TENSOR_MAP_SWIZZLE_128B : CU_TENSOR_MAP_SWIZZLE_32B, CU_TENSOR_MAP_L2_PROMOTION_NONE,
        CU_TENSOR_MAP_FLOAT_OOB_FILL_NONE);
}

}

extern "C" void kernel_launch(void* const* d_in, const int* in_sizes, int n_in, void* d_out, int out_size) {
    (void)in_sizes; (void)n_in; (void)out_size;
    static EncodeFn enc = nullptr;
    static unsigned char* acc = nullptr;
    static MlRow* ml = nullptr;
    if (!enc) {
        void* p = nullptr;
        cudaGetSymbolAddress(&p, g_acc_raw);
        acc = reinterpret_cast<unsigned char*>((reinterpret_cast<uintptr_t>(p) + 32767) & ~(uintptr_t)32767);
        cudaGetSymbolAddress(&p, g_ml_buf);
        ml = reinterpret_cast<MlRow*>(p);
        cudaDriverEntryPointQueryResult qr;
        void* fn = nullptr;
        cudaGetDriverEntryPoint("cuTensorMapEncodeTiled", &fn, cudaEnableDefault, &qr);
        enc = (EncodeFn)fn;
        cudaFuncSetAttribute(fused_kernel, cudaFuncAttributeMaxDynamicSharedMemorySize, (int)SMEM_BYTES);
    }
    Maps mp;
    make_map(enc, &mp.wq, d_in[3], 4096, 512, 64, 256);
    make_map(enc, &mp.k, d_in[1], 128, 32 * 4096, 64, 128);
    make_map(enc, &mp.v, d_in[2], 128, 32 * 4096, 64, 128);
    make_map(enc, &mp.wo, d_in[4], 512, 4096, 64, 64);
    make_map(enc, &mp.w1, d_in[6], 1376, 512, 16, 256);
    make_map(enc, &mp.w3, d_in[7], 1376, 512, 16, 256);
    make_map(enc, &mp.w2, d_in[8], 512, 1376, 64, 16);
    fused_kernel<<<NCTA, NTHR, SMEM_BYTES>>>((const __nv_bfloat16*)d_in[0], (__nv_bfloat16*)d_out, acc, ml, mp);
}
```

```cpp
#include <cuda_runtime.h>
#include <cuda_bf16.h>
#include <cuda.h>
#include <stdint.h>

namespace {

constexpr int NCTA = 128;
constexpr int NTHR = 256;
constexpr int NFFN = 86;
#define NWO0 4
#define NWO1 9
#define PD2 500u
#define PD3 480u
#define PDN 700u
#define QNS 155
#define LEAD 5
#define FQ 44
#define F2Q 50
#define P1NS 8800u
constexpr int SPIN_LIMIT = 1 << 22;

constexpr uint32_t OFF_WQ = 0;
constexpr uint32_t OFF_K = 65536;
constexpr uint32_t OFF_W13 = OFF_K + 5 * 8192;
constexpr uint32_t OFF_SX0 = OFF_K + 65536;
constexpr uint32_t OFF_WO5 = OFF_SX0 + 8192;
constexpr uint32_t OFF_V = OFF_WO5 + 24576;
constexpr uint32_t OFF_W2 = OFF_V;
constexpr uint32_t OFF_SX1 = OFF_V + 16384;
constexpr uint32_t OFF_FP = OFF_SX1 + 2048;
constexpr uint32_t OFF_FC = OFF_FP + 512;
constexpr uint32_t VS = 144;
constexpr uint32_t OFF_XS = OFF_V + 65536;
constexpr uint32_t OFF_PS = OFF_XS + 1152;
constexpr uint32_t OFF_QS = OFF_PS + 1152;
constexpr uint32_t OFF_OS = OFF_QS + 128;
constexpr uint32_t OFF_M = OFF_OS + 128;
constexpr uint32_t OFF_SQ = OFF_M + 32;
constexpr uint32_t OFF_BAR = OFF_SQ + 64;
constexpr uint32_t BS = 48;
constexpr uint32_t B_WQ = 0, B_K = 8, B_V = 16, B_WO = 24, B_F = 32, B_SX = 40;
constexpr uint32_t SMEM_BYTES = OFF_BAR + 8 * BS;
static_assert(SMEM_BYTES <= 232448, "smem");

struct Maps { CUtensorMap wq, k, v, wo, w1, w3, w2; };

typedef float2 MlRow[NCTA][16];
__device__ __align__(128) unsigned char g_acc_raw[65536];
__device__ __align__(128) float2 g_ml_buf[1][NCTA][16];
#define PROF_PARAM
#define STAMP(k) do {} while (0)

__device__ __forceinline__ void mbar_init(uint32_t a, int c) {
    asm volatile("mbarrier.init.shared::cta.b64 [%0], %1;" ::"r"(a), "r"(c) : "memory");
}
__device__ __forceinline__ void mbar_expect(uint32_t a, uint32_t bytes) {
    asm volatile("mbarrier.arrive.expect_tx.shared::cta.b64 _, [%0], %1;" ::"r"(a), "r"(bytes) : "memory");
}
__device__ __forceinline__ void mbar_wait(uint32_t a, uint32_t parity) {
    uint32_t ok;
    int n = 0;
    do {
        asm volatile("{\n.reg .pred p;\nmbarrier.try_wait.parity.shared::cta.b64 p, [%1], %2;\nselp.u32 %0, 1, 0, p;\n}"
                     : "=r"(ok) : "r"(a), "r"(parity) : "memory");
    } while (!ok && ++n < SPIN_LIMIT);
}
__device__ __forceinline__ bool mbar_test(uint32_t a) {
    uint32_t ok;
    asm volatile("{\n.reg .pred p;\nmbarrier.test_wait.parity.shared::cta.b64 p, [%1], 0;\nselp.u32 %0, 1, 0, p;\n}" : "=r"(ok) : "r"(a) : "memory");
    return ok;
}
__device__ __forceinline__ uint32_t gtime() {
    uint32_t c;
    asm volatile("mov.u32 %0, %%globaltimer_lo;" : "=r"(c) :: "memory");
    return __shfl_sync(0xffffffffu, c, 0);
}
__device__ __forceinline__ void tma2d(uint32_t dst, const CUtensorMap* m, int c0, int c1, uint32_t bar) {
    asm volatile("cp.async.bulk.tensor.2d.shared::cluster.global.mbarrier::complete_tx::bytes [%0], [%1, {%3, %4}], [%2];"
                 ::"r"(dst), "l"(m), "r"(bar), "r"(c0), "r"(c1) : "memory");
}
__device__ __forceinline__ void ldsm4(uint32_t* r, uint32_t a) {
    asm volatile("ldmatrix.sync.aligned.m8n8.x4.shared.b16 {%0,%1,%2,%3}, [%4];"
                 : "=r"(r[0]), "=r"(r[1]), "=r"(r[2]), "=r"(r[3]) : "r"(a) : "memory");
}
__device__ __forceinline__ void ldsm4t(uint32_t* r, uint32_t a) {
    asm volatile("ldmatrix.sync.aligned.m8n8.x4.trans.shared.b16 {%0,%1,%2,%3}, [%4];"
                 : "=r"(r[0]), "=r"(r[1]), "=r"(r[2]), "=r"(r[3]) : "r"(a) : "memory");
}
__device__ __forceinline__ void mma(float* c, const uint32_t* a, uint32_t b0, uint32_t b1) {
    asm("mma.sync.aligned.m16n8k16.row.col.f32.bf16.bf16.f32 {%0,%1,%2,%3},{%4,%5,%6,%7},{%8,%9},{%0,%1,%2,%3};"
        : "+f"(c[0]), "+f"(c[1]), "+f"(c[2]), "+f"(c[3])
        : "r"(a[0]), "r"(a[1]), "r"(a[2]), "r"(a[3]), "r"(b0), "r"(b1));
}
__device__ __forceinline__ uint4 lds128(uint32_t a) {
    uint4 v;
    asm volatile("ld.shared.v4.u32 {%0,%1,%2,%3}, [%4];" : "=r"(v.x), "=r"(v.y), "=r"(v.z), "=r"(v.w) : "r"(a) : "memory");
    return v;
}
__device__ __forceinline__ float4 lds128f(uint32_t a) {
    float4 v;
    asm volatile("ld.shared.v4.f32 {%0,%1,%2,%3}, [%4];" : "=f"(v.x), "=f"(v.y), "=f"(v.z), "=f"(v.w) : "r"(a) : "memory");
    return v;
}
__device__ __forceinline__ float2 lds64f(uint32_t a) {
    float2 v;
    asm volatile("ld.shared.v2.f32 {%0,%1}, [%2];" : "=f"(v.x), "=f"(v.y) : "r"(a) : "memory");
    return v;
}
__device__ __forceinline__ float lds32f(uint32_t a) {
    float v;
    asm volatile("ld.shared.f32 %0, [%1];" : "=f"(v) : "r"(a) : "memory");
    return v;
}
__device__ __forceinline__ void sts16(uint32_t a, uint32_t v) {
    asm volatile("st.shared.u16 [%0], %1;" ::"r"(a), "h"((unsigned short)v) : "memory");
}
__device__ __forceinline__ void sts32f(uint32_t a, float v) {
    asm volatile("st.shared.f32 [%0], %1;" ::"r"(a), "f"(v) : "memory");
}
__device__ __forceinline__ void cta_sync() { asm volatile("bar.sync 0;" ::: "memory"); }
__device__ __forceinline__ float ex2(float x) {
    float y;
    asm("ex2.approx.ftz.f32 %0, %1;" : "=f"(y) : "f"(x));
    return y;
}
__device__ __forceinline__ float rcp(float x) {
    float y;
    asm("rcp.approx.ftz.f32 %0, %1;" : "=f"(y) : "f"(x));
    return y;
}
__device__ __forceinline__ uint32_t pack_bf16(float lo, float hi) {
    uint32_t r;
    asm("cvt.rn.bf16x2.f32 %0, %1, %2;" : "=r"(r) : "f"(hi), "f"(lo));
    return r;
}
__device__ __forceinline__ float4 ld_relaxed4(const void* p) {
    float4 v;
    asm volatile("ld.relaxed.gpu.global.v4.f32 {%0,%1,%2,%3}, [%4];" : "=f"(v.x), "=f"(v.y), "=f"(v.z), "=f"(v.w) : "l"(p) : "memory");
    return v;
}
__device__ __forceinline__ float2 ld_relaxed2(const void* p) {
    float2 v;
    asm volatile("ld.relaxed.gpu.global.v2.f32 {%0,%1}, [%2];" : "=f"(v.x), "=f"(v.y) : "l"(p) : "memory");
    return v;
}
__device__ __forceinline__ void st_relaxed2(void* p, float x, float y) {
    asm volatile("st.relaxed.gpu.global.v2.f32 [%0], {%1,%2};" ::"l"(p), "f"(x), "f"(y) : "memory");
}
__device__ __forceinline__ void st_relaxed4(void* p, float x, float y, float z, float w) {
    asm volatile("st.relaxed.gpu.global.v4.f32 [%0], {%1,%2,%3,%4};" ::"l"(p), "f"(x), "f"(y), "f"(z), "f"(w) : "memory");
}
__device__ __forceinline__ void red4(void* p, float x, float y, float z, float w) {
    asm volatile("red.relaxed.gpu.global.add.v4.f32 [%0], {%1,%2,%3,%4};" ::"l"(p), "f"(x), "f"(y), "f"(z), "f"(w) : "memory");
}
__device__ __forceinline__ float4 atom4(void* p, float x, float y, float z, float w) {
    float4 v;
    asm volatile("atom.relaxed.gpu.global.add.v4.f32 {%0,%1,%2,%3}, [%4], {%5,%6,%7,%8};"
                 : "=f"(v.x), "=f"(v.y), "=f"(v.z), "=f"(v.w) : "l"(p), "f"(x), "f"(y), "f"(z), "f"(w) : "memory");
    return v;
}
__device__ __forceinline__ constexpr uint32_t eoff(int e) { return (uint32_t)((e & 1) * 128 + (e >> 1) * 512); }

constexpr uint32_t ONES = 0x3F803F80u;

__device__ __forceinline__ void mma_ab(float* c, uint32_t a0, uint32_t a1, uint32_t a2, uint32_t a3, uint32_t b0, uint32_t b1) {
    asm("mma.sync.aligned.m16n8k16.row.col.f32.bf16.bf16.f32 {%0,%1,%2,%3},{%4,%5,%6,%7},{%8,%9},{%0,%1,%2,%3};"
        : "+f"(c[0]), "+f"(c[1]), "+f"(c[2]), "+f"(c[3])
        : "r"(a0), "r"(a1), "r"(a2), "r"(a3), "r"(b0), "r"(b1));
}
__device__ __forceinline__ bool elect_one() {
    uint32_t p;
    asm volatile("{\n.reg .pred p;\nelect.sync _|p, 0xffffffff;\nselp.u32 %0, 1, 0, p;\n}" : "=r"(p));
    return p;
}
__device__ __forceinline__ float rsq(float x) {
    float y;
    asm("rsqrt.approx.ftz.f32 %0, %1;" : "=f"(y) : "f"(x));
    return y;
}
__device__ __forceinline__ uint32_t elapsed(uint32_t c0) {
    uint32_t c;
    asm volatile("mov.u32 %0, %%clock;" : "=r"(c) :: "memory");
    return __shfl_sync(0xffffffffu, c, 0) - c0 ;
}
__device__ __forceinline__ void zero4(float* c) { c[0] = c[1] = c[2] = c[3] = 0.f; }
__device__ __forceinline__ uint32_t pin(uint32_t v, int lane) { return __shfl_sync(0xffffffffu, v, lane); }

__device__ __forceinline__ void ln_partials(const uint4& u0, const uint4& u1, bool godd, float& s, float& q) {
    float c[4], d[4];
    zero4(c); zero4(d);
    mma_ab(c, u0.x, ONES, u0.y, ONES, u0.x, u0.y);
    mma_ab(d, u1.x, ONES, u1.y, ONES, u1.x, u1.y);
    mma_ab(c, u0.z, ONES, u0.w, ONES, u0.z, u0.w);
    mma_ab(d, u1.z, ONES, u1.w, ONES, u1.z, u1.w);
    s = (c[2] + d[2]) + (c[3] + d[3]);
    q = godd ? c[1] + d[1] : c[0] + d[0];
}
__device__ __forceinline__ void ln_finish(float s, float q, float& mean, float& rstd) {
    q += __shfl_xor_sync(0xffffffffu, q, 4);
    s += __shfl_xor_sync(0xffffffffu, s, 1);
    q += __shfl_xor_sync(0xffffffffu, q, 9);
    s += __shfl_xor_sync(0xffffffffu, s, 2);
    q += __shfl_xor_sync(0xffffffffu, q, 18);
    mean = s * (1.f / 512.f);
    q = __shfl_sync(0xffffffffu, q, 0);
    rstd = rsq(fmaxf(fmaf(-mean, mean, q * (1.f / 512.f)), 0.f) + 1e-5f);
}

#define FENCE() __syncwarp()
#define DEP2(x, d1, d2) ((x) | (((d1) | (d2)) & zr))
#define WO_FRAG(j) ldsm4t(Wf[j], (a_wo ^ (((j) & 3) << 5)) + ((j) >> 2) * 2048)

__global__ void __cluster_dims__(2, 1, 1) __launch_bounds__(NTHR, 1)
fused_kernel(const __nv_bfloat16* __restrict__ x_in, __nv_bfloat16* __restrict__ out, unsigned char* const acc_base, MlRow* const g_ml,
             PROF_PARAM const __grid_constant__ Maps mp) {
    extern __shared__ __align__(1024) unsigned char smem[];
    const uint32_t sb = (uint32_t)__cvta_generic_to_shared(smem);
    const int tid = threadIdx.x;
    const int b = blockIdx.x, r = b & 1, pr = (b >> 1) & 1, h = b >> 2;
    unsigned clk0;
    asm volatile("mov.u32 %0, %%clock;" : "=r"(clk0) :: "memory");
    if (tid == 0) {
        mbar_init(sb + OFF_BAR + B_WQ, 1);
        asm volatile("fence.mbarrier_init.release.cluster;" ::: "memory");
        mbar_expect(sb + OFF_BAR + B_WQ, 65536 + 1024);
        asm volatile("cp.async.bulk.shared::cluster.global.mbarrier::complete_tx::bytes [%0], [%1], 1024, [%2];"
                     ::"r"(sb + OFF_PS), "l"(x_in), "r"(sb + OFF_BAR + B_WQ) : "memory");
        tma2d(sb + OFF_WQ, &mp.wq, h * 128 + r * 64, 0, sb + OFF_BAR + B_WQ);
        tma2d(sb + OFF_WQ + 32768, &mp.wq, h * 128 + r * 64, 256, sb + OFF_BAR + B_WQ);
    }
    const uint32_t g0 = gtime();
    clk0 = __shfl_sync(0xffffffffu, clk0, 0);
    const int w = __shfl_sync(0xffffffffu, tid >> 5, 0), lane = tid & 31, g = lane >> 2, t = lane & 3;
    const bool ffn = b < NFFN;
    const uint32_t bars = sb + OFF_BAR + w * BS;
    if (elect_one()) {
        if (w >= 1 && w < 7) asm volatile("prefetch.tensormap [%0];" ::"l"(&mp.wq + w) : "memory");
        mbar_init(bars + B_K, 1); mbar_init(bars + B_V, 1); mbar_init(bars + B_WO, 1); mbar_init(bars + B_F, 1); mbar_init(bars + B_SX, 1);
        asm volatile("fence.mbarrier_init.release.cluster;" ::: "memory");
        mbar_expect(bars + B_SX, 256);
    }
    __syncwarp();
    STAMP(13);
    asm volatile("barrier.cluster.arrive.relaxed.aligned;" ::: "memory");

    unsigned char* const accp = acc_base + pin(w * 4096 + (g >> 1) * 1024 + ((g & 1) * 3 + (t < 3 ? t : 2)) * 16, lane);
    unsigned char* const accw = accp + r * 256;
    const bool own = t < 3;
    uint32_t zdep = 0;
    {
        const int z = tid - 32;
        unsigned char* zp;
        if (z < 16) zp = reinterpret_cast<unsigned char*>(&g_ml[0][b][0]) + (z >> 1) * 16 + 8 + (z & 1) * 4;
        else {
            const int i = b * 48 + (z - 16), e = 1 + (i >> 11), u = (i >> 5) & 63;
            zp = acc_base + (u >> 3) * 4096 + (u & 1) * 256 + ((u >> 1) & 3) * 1024 + (e & 1) * 128 + (e >> 1) * 512 + (i & 31) * 4;
        }
        asm volatile("{\n.reg .pred p;\nsetp.lt.u32 p, %2, 64;\n@p atom.relaxed.gpu.global.exch.b32 %0, [%1], 0;\n}"
                     : "+r"(zdep) : "l"(zp), "r"(z) : "memory");
    }

    const int mi = lane >> 3, li = lane & 7;
    const uint32_t wo_box = sb + (w < 5 ? OFF_K + w * 8192 : OFF_WO5 + (w - 5) * 8192);
    const uint32_t a_gemv = pin(sb + ((mi & 1) * 64 + (mi >> 1) * 8 + li) * 128 + ((w ^ li) << 4), lane);
    const uint32_t a_wo = pin(wo_box + ((mi >> 1) * 8 + li) * 128 + (((mi & 1) ^ li) << 4), lane);
    const uint32_t a_xst = pin(sb + OFF_XS + w * VS + (g >> 1) * 32 + (g & 1) * 2 + t * 12, lane);
    const uint32_t a_pst = pin(sb + OFF_PS + w * VS + (g >> 1) * 32 + (g & 1) * 2 + t * 8, lane);
    const uint32_t a_row = pin(sb + g * VS + t * 32, lane);
    const uint32_t a_qo = pin(sb + (g >> 1) * 32 + w * 4 + (g & 1) * 2, lane);
    const uint32_t a_t32 = pin(sb + t * 32, lane);
    const uint32_t a_sx = pin(sb + tid * 8, lane);
    uint32_t peer_sx, peer_bar;
    asm volatile("mapa.shared::cluster.u32 %0, %1, %2;" : "=r"(peer_sx) : "r"(a_sx), "r"(r ^ 1));
    asm volatile("mapa.shared::cluster.u32 %0, %1, %2;" : "=r"(peer_bar) : "r"(bars + B_SX), "r"(r ^ 1));
    const float2* const mlp = &g_ml[0][0][0] + pin((b ^ 2) * 16 + 2 * g, lane);
    float2* const mlo = &g_ml[0][0][0] + pin(b * 16 + 2 * g, lane);
    const uint32_t a_mg = pin(sb + OFF_M + g * 4, lane), a_mt = pin(sb + OFF_M + t * 8, lane), a_sb = pin(sb, lane), a_bsx = pin(bars + B_SX, lane);
    const uint32_t zr = pin(tid >> 20, lane);

    int todo = 1, vi = 0;
    uint32_t due = (uint32_t)((8 + 2 * w - LEAD) * QNS);
    const int kr = h * 4096 + 3072 + pr * 512;
    auto issue = [&]() {
        const bool el = elect_one();
        if (todo == 1) {
            if (el) { mbar_expect(bars + B_K, 8192); tma2d(sb + OFF_K + w * 8192, &mp.k, r * 64, kr + w * 64, bars + B_K); }
            todo = 0;
        } else if (todo == 2) {
            if (el) {
                const uint32_t bar = sb + OFF_BAR + (vi >> 1) * BS + B_V;
                if (!(vi & 1)) mbar_expect(bar, 16384);
                tma2d(sb + OFF_V + vi * 8192, &mp.v, r * 64, kr + vi * 64, bar);
            }
            vi++; due += 2 * QNS;
            if (vi == 8) todo = 0;
        } else if (todo == 3) {
            if (el) { mbar_expect(bars + B_WO, 8192); tma2d(wo_box, &mp.wo, w * 64, h * 128 + r * 64, bars + B_WO); }
            todo = (ffn && w < 4) ? 4 : 0;
            due = (uint32_t)((FQ - LEAD) * QNS + w * (4 * QNS / 3));
        } else if (todo == 4) {
            if (el) { mbar_expect(bars + B_F, 8192); tma2d(sb + OFF_W13 + w * 8192, (w & 1) ? &mp.w3 : &mp.w1, b * 16, (w >> 1) * 256, bars + B_F); }
            todo = 0;
        } else {
            if (el) {
                mbar_expect(bars + B_F, 4096);
                tma2d(sb + OFF_W2 + (w - 4) * 4096, &mp.w2, (w - 4) * 128, b * 16, bars + B_F);
                tma2d(sb + OFF_W2 + (w - 4) * 4096 + 2048, &mp.w2, (w - 4) * 128 + 64, b * 16, bars + B_F);
            }
            todo = 0;
        }
        __syncwarp();
    };
    auto gated_wait = [&](uint32_t bar) {
        int n = SPIN_LIMIT;
        while (todo) {
            if (gtime() - g0 >= due) issue();
            if (mbar_test(bar) || --n < 0) return;
        }
        mbar_wait(bar, 0);
    };
    uint32_t Kf[16][4], Vf[16][4], S[16][4], Wf[16][4];
    float cs_q = 0.f, cs_g = 0.f, cs_u = 0.f;
    STAMP(0);
    asm volatile("barrier.cluster.wait.acquire.aligned;" ::: "memory");
    gated_wait(sb + OFF_BAR + B_WQ);
    if (todo) issue();
    STAMP(14);
    float xo[3];
#pragma unroll
    for (int i = 0; i < 3; i++) {
        uint32_t xr;
        asm volatile("ld.shared.u16 %0, [%1];" : "=r"(xr) : "r"(sb + OFF_PS + (64 * w + 8 * ((3 * t + i) & 7) + g) * 2) : "memory");
        xo[i] = __uint_as_float(xr << 16);
    }

    uint32_t p01 = 0, p2 = 0;
    auto put_x = [&](float vx, float vy, float vz) {
        p01 = pack_bf16(xo[0] + vx, xo[1] + vy);
        p2 = pack_bf16(xo[2] + vz, 0.f);
        if (own) { sts16(a_xst, p01); sts16(a_xst + 4, p01 >> 16); }
        if (t < 2) sts16(a_xst + 8, p2);
    };
    auto commit_x = [&]() {
        cta_sync();
        xo[0] = __uint_as_float(p01 << 16); xo[1] = __uint_as_float(p01 & 0xffff0000u); xo[2] = __uint_as_float(p2 << 16);
    };
    uint32_t t_red = 0;
    auto exchange_wait = [&](const unsigned char* p, float target, uint32_t delay) {
        int n = SPIN_LIMIT;
        if (delay) while (elapsed(t_red) < delay) {}
        bool more;
        do {
            const float4 v = ld_relaxed4(p), v2 = ld_relaxed4(p + 256);
            --n;
            more = __any_sync(0xffffffffu, v.w + v2.w != target && n > 0);
            put_x(v.x + v2.x, v.y + v2.y, v.z + v2.z);
        } while (more);
        commit_x();
    };

#pragma unroll
    for (int layer = 0; layer < 2; layer++) {
#pragma unroll
        for (int j = 0; j < 16; j++) ldsm4t(S[j], a_gemv + OFF_WQ + ((j >> 2) * 128 + (j & 3) * 16) * 128);
        if (layer == 0) {
            float c0[4], c1[4];
            zero4(c0); zero4(c1);
#pragma unroll
            for (int j = 0; j < 8; j++) { mma(c0, S[2 * j], ONES, ONES); mma(c1, S[2 * j + 1], ONES, ONES); }
            cs_q = ((c0[0] + c0[3]) + (c1[0] + c1[3])) * (1.f / 512.f);
            put_x(0.f, 0.f, 0.f);
            commit_x();
            if (b < 2 && own) red4(accw, 0.5f * xo[0], 0.5f * xo[1], t < 2 ? 0.5f * xo[2] : 0.f, 1.f);
            xo[0] = xo[1] = xo[2] = 0.f;
        } else {
            if (!ffn) { while (gtime() - g0 < P1NS) {} exchange_wait(accp + eoff(0), (float)(NCTA + 2), 0); t_red = elapsed(0) + PDN; if (PDN) while ((int)elapsed(t_red) < 0) {} }
            exchange_wait(accp + eoff(1), (float)NFFN, PD2);
        }
        STAMP(1 + layer * 14);
        float ls, lq;
        {
            uint4 u0 = lds128(a_row + OFF_XS), u1 = lds128(a_row + OFF_XS + 16);
            float acc[4][4];
#pragma unroll
            for (int a = 0; a < 4; a++) { zero4(acc[a]); mma(acc[a], S[a * 4 + 0], u0.x, u0.y); }
            ln_partials(u0, u1, g & 1, ls, lq);
#pragma unroll
            for (int a = 0; a < 4; a++) mma(acc[a], S[a * 4 + 1], u0.z, u0.w);
#pragma unroll
            for (int a = 0; a < 4; a++) mma(acc[a], S[a * 4 + 2], u1.x, u1.y);
#pragma unroll
            for (int a = 0; a < 4; a++) mma(acc[a], S[a * 4 + 3], u1.z, u1.w);
            float e0 = (t & 2) ? ((t & 1) ? acc[3][0] : acc[2][0]) : ((t & 1) ? acc[1][0] : acc[0][0]);
            float e1 = (t & 2) ? ((t & 1) ? acc[3][3] : acc[2][3]) : ((t & 1) ? acc[1][3] : acc[0][3]);
            float q = fmaf(-ls, cs_q, e0) + e1;
            q += __shfl_xor_sync(0xffffffffu, q, 1);
            q += __shfl_xor_sync(0xffffffffu, q, 2);
            if (t == 0) sts16(a_qo + OFF_QS, pack_bf16(q, 0.f));
        }
        STAMP(2 + layer * 14);
        cta_sync();
        if (layer == 0) {
            if (w == 7) { todo = 2; due = (uint32_t)((24 - LEAD) * QNS); }
            gated_wait(bars + B_K);
            while (todo) issue();
#pragma unroll
            for (int j = 0; j < 16; j++)
                ldsm4(Kf[j], sb + OFF_K + w * 8192 + ((j >> 2) * 16 + (mi & 1) * 8 + li) * 128 + ((((j & 3) * 2 + (mi >> 1)) ^ li) << 4));
        }
        float s0, s1, scl;
        {
            uint4 q0 = lds128(a_t32 + OFF_QS), q1 = lds128(a_t32 + OFF_QS + 16);
            float sc[4][4];
#pragma unroll
            for (int j = 0; j < 4; j++) { zero4(sc[j]); mma(sc[j], Kf[j * 4 + 0], q0.x, q0.y); }
#pragma unroll
            for (int j = 0; j < 4; j++) mma(sc[j], Kf[j * 4 + 1], q0.z, q0.w);
#pragma unroll
            for (int j = 0; j < 4; j++) mma(sc[j], Kf[j * 4 + 2], q1.x, q1.y);
#pragma unroll
            for (int j = 0; j < 4; j++) mma(sc[j], Kf[j * 4 + 3], q1.z, q1.w);
            float mean, rstd;
            ln_finish(ls, lq, mean, rstd);
            scl = rstd * (0.08838834764831845f * 1.4426950408889634f);
            s0 = (t & 2) ? ((t & 1) ? sc[3][0] : sc[2][0]) : ((t & 1) ? sc[1][0] : sc[0][0]);
            s1 = (t & 2) ? ((t & 1) ? sc[3][2] : sc[2][2]) : ((t & 1) ? sc[1][2] : sc[0][2]);
            asm volatile("st.async.weak.shared::cluster.mbarrier::complete_tx::bytes.v2.f32 [%0], {%1,%2}, [%3];"
                         ::"r"(peer_sx + (layer ? OFF_SX1 : OFF_SX0)), "f"(s0), "f"(s1), "r"(peer_bar) : "memory");
            FENCE();
            if (layer == 1) {
#pragma unroll
                for (int j = NWO0; j < NWO1; j++) WO_FRAG(j);
            }
        }
        STAMP(3 + layer * 14);
        s0 *= scl; s1 *= scl;
        mbar_wait(a_bsx, layer);
        {
            float2 o2 = lds64f(a_sx + (layer ? OFF_SX1 : OFF_SX0));
            s0 = fmaf(o2.x, scl, s0);
            s1 = fmaf(o2.y, scl, s1);
            int mi_ = __float_as_int(fmaxf(fmaxf(s0, s1), -3.0e38f));
            mi_ ^= (mi_ >> 31) & 0x7fffffff;
            mi_ = __reduce_max_sync(0xffffffffu, mi_);
            mi_ ^= (mi_ >> 31) & 0x7fffffff;
            const float mw = __int_as_float(mi_);
            uint32_t pp = pack_bf16(ex2(s0 - mw), ex2(s1 - mw));
            sts16(a_pst, pp);
            sts16(a_pst + 4, pp >> 16);
            if (lane == 0) sts32f(a_qo + OFF_M, mw);
        }
        STAMP(4 + layer * 14);
        cta_sync();
        float M, tot;
        float2 rem, rem2;
        {
            uint4 u0 = lds128(a_row + OFF_PS), u1 = lds128(a_row + OFF_PS + 16);
            float mg = lds32f(a_mg);
            FENCE();
            float4 m0 = lds128f(a_sb + OFF_M), m1 = lds128f(a_sb + OFF_M + 16);
            float2 mt = lds64f(a_mt);
            if (w == 0) {
                float c[4], d[4];
                zero4(c); zero4(d);
                mma_ab(c, u0.x, u0.y, u0.z, u0.w, ONES, ONES);
                mma_ab(d, u1.x, u1.y, u1.z, u1.w, ONES, ONES);
                const float l0 = (c[1] + c[3]) + (d[1] + d[3]);
                if (t == 0) st_relaxed2(mlo + layer, mg, __uint_as_float(__float_as_uint(l0) | 0x80000000u));
                __syncwarp();
            }
            float acc[4][4];
            if (layer == 0) {
                if (lane == 0) mbar_expect(bars + B_SX, 256);
                asm volatile("{\n.reg .pred p;\nsetp.eq.u32 p, %0, 0x7fd3a5c1;\n@p nanosleep.u32 1;\n}" ::"r"(zdep) : "memory");
                todo = 3; due = (uint32_t)((40 - LEAD) * QNS + w * (QNS / 2));
#pragma unroll
                for (int a = 0; a < 4; a++) {
                    if (a == 1) rem = ld_relaxed2(mlp);
                    gated_wait(sb + OFF_BAR + a * BS + B_V);
                    if (a == 3) STAMP(27);
#pragma unroll
                    for (int j = 0; j < 4; j++) ldsm4t(Vf[a * 4 + j], a_gemv + OFF_V + (a * 128 + j * 16) * 128);
                    zero4(acc[a]);
                    mma(acc[a], Vf[a * 4 + 0], u0.x, u0.y);
                    mma(acc[a], Vf[a * 4 + 1], u0.z, u0.w);
                    mma(acc[a], Vf[a * 4 + 2], u1.x, u1.y);
                    mma(acc[a], Vf[a * 4 + 3], u1.z, u1.w);
                }
            } else {
#pragma unroll
                for (int a = 0; a < 4; a++) { zero4(acc[a]); mma(acc[a], Vf[a * 4 + 0], u0.x, u0.y); }
                WO_FRAG(NWO1); WO_FRAG(NWO1 + 1); WO_FRAG(NWO1 + 2); WO_FRAG(NWO1 + 3);
                const uint32_t d0 = __float_as_uint(acc[3][1]);
                m0.x = __uint_as_float(DEP2(__float_as_uint(m0.x), d0, d0)); m0.z = __uint_as_float(DEP2(__float_as_uint(m0.z), d0, d0));
                m1.x = __uint_as_float(DEP2(__float_as_uint(m1.x), d0, d0)); m1.z = __uint_as_float(DEP2(__float_as_uint(m1.z), d0, d0));
#pragma unroll
                for (int a = 0; a < 4; a++) mma(acc[a], Vf[a * 4 + 1], u0.z, u0.w);
#pragma unroll
                for (int a = 0; a < 4; a++) mma(acc[a], Vf[a * 4 + 2], u1.x, u1.y);
                uint32_t bz = DEP2(u1.z, Wf[NWO1][0], Wf[NWO1 + 1][0]), bw = DEP2(u1.w, Wf[NWO1 + 2][0], Wf[NWO1 + 3][0]);
#pragma unroll
                for (int a = 0; a < 4; a++) mma(acc[a], Vf[a * 4 + 3], bz, bw);
            }
            M = fmaxf(fmaxf(fmaxf(m0.x, m0.y), fmaxf(m0.z, m0.w)), fmaxf(fmaxf(m1.x, m1.y), fmaxf(m1.z, m1.w)));
            {
                float c[4];
                zero4(c);
                mma_ab(c, u0.x, u0.y, u0.z, u0.w, ONES, ONES);
                mma_ab(c, u1.x, u1.y, u1.z, u1.w, ONES, ONES);
                tot = (c[0] + c[2]) * ex2(mg - M);
            }
            const float f0 = ex2(mt.x - M), f1 = ex2(mt.y - M);
            float e0 = (t & 2) ? ((t & 1) ? acc[3][0] : acc[2][0]) : ((t & 1) ? acc[1][0] : acc[0][0]);
            float e1 = (t & 2) ? ((t & 1) ? acc[3][3] : acc[2][3]) : ((t & 1) ? acc[1][3] : acc[0][3]);
            float o = fmaf(f0, e0, f1 * e1);
            if (layer == 1) { FENCE(); rem = ld_relaxed2(mlp + 1); }
            o += __shfl_xor_sync(0xffffffffu, o, 1);
            o += __shfl_xor_sync(0xffffffffu, o, 2);
            if (t == 0) sts16(a_qo + OFF_OS, pack_bf16(o, 0.f));
        }
        STAMP(5 + layer * 14);
        cta_sync();
        if (layer == 0) {
            if (todo == 3) issue();
            if (w >= 4 && ffn) { todo = 5; due = (uint32_t)((F2Q - LEAD) * QNS); }
            gated_wait(bars + B_WO);
            STAMP(28);
#pragma unroll
            for (int j = 0; j < NWO1 + 4; j++) WO_FRAG(j);
        }
        {
            uint4 o0 = lds128(a_t32 + OFF_OS), o1 = lds128(a_t32 + OFF_OS + 16);
#pragma unroll
            for (int j = NWO1 + 4; j < 16; j++) WO_FRAG(j);
            if (layer == 1) rem2 = ld_relaxed2(mlp + 1); else rem2 = rem;
            FENCE();
            float y[4][4];
#pragma unroll
            for (int j = 0; j < 4; j++) { zero4(y[j]); mma(y[j], Wf[j], o0.x, o0.y); }
#pragma unroll
            for (int j = 0; j < 4; j++) mma(y[j], Wf[4 + j], o0.z, o0.w);
#pragma unroll
            for (int j = 0; j < 4; j++) mma(y[j], Wf[8 + j], o1.x, o1.y);
#pragma unroll
            for (int j = 0; j < 4; j++) mma(y[j], Wf[12 + j], o1.z, o1.w);
            FENCE();
            STAMP(6 + layer * 14);
            if (!__all_sync(0xffffffffu, __float_as_uint(rem.y) != 0u)) {
                rem = rem2;
                int n = 0;
                while (!__all_sync(0xffffffffu, __float_as_uint(rem.y) != 0u) && ++n < SPIN_LIMIT) rem = ld_relaxed2(mlp + layer);
            }
            tot = fmaf(-rem.y, ex2(rem.x - M), tot);
            tot += __shfl_xor_sync(0xffffffffu, tot, 4);
            tot += __shfl_xor_sync(0xffffffffu, tot, 8);
            tot += __shfl_xor_sync(0xffffffffu, tot, 16);
            const float inv = rcp(tot);
            float v0 = (t == 0) ? y[0][0] : (t == 1) ? y[1][2] : y[3][0];
            float v1 = (t == 0) ? y[0][2] : (t == 1) ? y[2][0] : y[3][2];
            float v2 = (t == 0) ? y[1][0] : (t == 1) ? y[2][2] : 0.f;
            if (own) red4(accw + layer * eoff(2), v0 * inv, v1 * inv, v2 * inv, 1.f);
            t_red = elapsed(0);
            if (layer == 1 && w == 0 && t == 0) st_relaxed2(mlo, 0.f, 0.f);
        }
        STAMP(7 + layer * 14);

        if (ffn) {
            const uint32_t a_fst = pin(sb + OFF_FP + (w >> 2) * 256 + ((w & 1) * 8 + g) * 16 + ((w >> 1) & 1) * 8, lane);
            const bool fst = t == (w >> 1);
            const uint32_t a_frd = pin(sb + OFF_FP + (lane & 15) * 16, lane);
            const uint32_t a_w2 = sb + OFF_W2 + w * 2048 + ((mi >> 1) * 8 + li) * 128 + (((mi & 1) ^ li) << 4);
            if (layer == 0) {
                while (todo) if (gtime() - g0 >= due) issue();
            }
            const uint32_t a_w13 = sb + OFF_W13 + (w >> 2) * 16384 + (mi & 1) * 8192 + (((w >> 1) & 1) * 128 + (mi >> 1) * 8 + li) * 32 + (((w & 1) ^ (li >> 2)) << 4);
            auto stage_w13 = [&]() {
#pragma unroll
                for (int j = 0; j < 8; j++) ldsm4t(S[j], a_w13 + j * 16 * 32);
                if (layer == 0) {
                    float c0[4], c1[4];
                    zero4(c0); zero4(c1);
#pragma unroll
                    for (int j = 0; j < 4; j++) { mma(c0, S[2 * j], ONES, ONES); mma(c1, S[2 * j + 1], ONES, ONES); }
                    if (t == 0) asm volatile("st.shared.v2.f32 [%0], {%1,%2};" ::"r"(a_fst + (OFF_FC - OFF_FP)), "f"(c0[0] + c1[0]), "f"(c0[2] + c1[2]) : "memory");
                }
            };
            if (layer == 0) {
                const uint32_t bw1 = sb + OFF_BAR + (w >> 2) * 2 * BS + B_F;
                bool staged = false, more;
                int n = SPIN_LIMIT;
                while (gtime() - g0 < P1NS) {
                    if (!staged && mbar_test(bw1) && mbar_test(bw1 + BS)) { stage_w13(); staged = true; }
                }
                do {
                    const float4 v = ld_relaxed4(accp), v2 = ld_relaxed4(accp + 256);
                    if (!staged && mbar_test(bw1) && mbar_test(bw1 + BS)) { stage_w13(); staged = true; }
                    --n;
                    more = __any_sync(0xffffffffu, v.w + v2.w != (float)(NCTA + 2) && n > 0);
                    put_x(v.x + v2.x, v.y + v2.y, v.z + v2.z);
                } while (more);
                STAMP(8);
                if (!staged) { mbar_wait(bw1, 0); mbar_wait(bw1 + BS, 0); STAMP(29); stage_w13(); }
                commit_x();
            } else {
                stage_w13();
#pragma unroll
                for (int j = 0; j < 4; j++) ldsm4t(S[8 + j], a_w2 ^ (j << 5));
                STAMP(8 + layer * 14);
                exchange_wait(accp + eoff(2), (float)NCTA, PD3);
            }
            STAMP(9 + layer * 14);
            {
                uint4 u0 = lds128(a_row + OFF_XS), u1 = lds128(a_row + OFF_XS + 16);
                if (layer == 0) {
                    float4 p0 = lds128f(a_frd + (OFF_FC - OFF_FP)), p1 = lds128f(a_frd + (OFF_FC - OFF_FP) + 256);
                    cs_g = (p0.x + p0.z) + (p1.x + p1.z);
                    cs_u = (p0.y + p0.w) + (p1.y + p1.w);
                }
                {
                    const uint32_t z0 = own ? p01 : 0u, z1 = t < 2 ? p2 : 0u;
                    float c[4];
                    zero4(c);
                    mma_ab(c, z0, ONES, z1, ONES, z0, z1);
                    float s_ = c[2] + c[3], q_ = (g & 1) ? c[1] : c[0];
                    q_ += __shfl_xor_sync(0xffffffffu, q_, 4);
                    s_ += __shfl_xor_sync(0xffffffffu, s_, 1);
                    q_ += __shfl_xor_sync(0xffffffffu, q_, 9);
                    s_ += __shfl_xor_sync(0xffffffffu, s_, 2);
                    q_ += __shfl_xor_sync(0xffffffffu, q_, 18);
                    if (lane == 0) { sts32f(a_qo + OFF_SQ, s_); sts32f(a_qo + OFF_SQ + 32, q_); }
                }
                float acc[4][4];
                zero4(acc[0]); zero4(acc[1]); zero4(acc[2]); zero4(acc[3]);
                mma(acc[0], S[0], u0.x, u0.y); mma(acc[1], S[4], u0.x, u0.y); mma(acc[2], S[2], u1.x, u1.y); mma(acc[3], S[6], u1.x, u1.y);
                mma(acc[0], S[1], u0.z, u0.w); mma(acc[1], S[5], u0.z, u0.w); mma(acc[2], S[3], u1.z, u1.w); mma(acc[3], S[7], u1.z, u1.w);
                if (fst) asm volatile("st.shared.v2.f32 [%0], {%1,%2};" ::"r"(a_fst), "f"((acc[0][0] + acc[2][0]) + (acc[1][1] + acc[3][1])),
                                      "f"((acc[0][2] + acc[2][2]) + (acc[1][3] + acc[3][3])) : "memory");
            }
            STAMP(10 + layer * 14);
            cta_sync();
            {
                const float4 s0 = lds128f(a_sb + OFF_SQ), s1 = lds128f(a_sb + OFF_SQ + 16), q0 = lds128f(a_sb + OFF_SQ + 32), q1 = lds128f(a_sb + OFF_SQ + 48);
                float4 p0 = lds128f(a_frd), p1 = lds128f(a_frd + 256);
                const float mean2 = (((s0.x + s0.y) + (s0.z + s0.w)) + ((s1.x + s1.y) + (s1.z + s1.w))) * (1.f / 512.f);
                const float ssq = ((q0.x + q0.y) + (q0.z + q0.w)) + ((q1.x + q1.y) + (q1.z + q1.w));
                const float rstd2 = rsq(fmaxf(fmaf(-mean2, mean2, fmaf(ssq, 1.f / 512.f, 1e-5f)), 1e-5f));
                if (layer == 0) {
                    mbar_wait(sb + OFF_BAR + (4 + (w >> 1)) * BS + B_F, 0);
#pragma unroll
                    for (int j = 0; j < 4; j++) ldsm4t(S[8 + j], a_w2 ^ (j << 5));
                }
                float gate = rstd2 * (fmaf(-mean2, cs_g, p0.x + p0.z) + (p1.x + p1.z));
                float up = rstd2 * (fmaf(-mean2, cs_u, p0.y + p0.w) + (p1.y + p1.w));
                float hv = gate * up * rcp(1.f + ex2(-1.4426950408889634f * gate));
                float h0 = __shfl_sync(0xffffffffu, hv, 2 * t), h1 = __shfl_sync(0xffffffffu, hv, 2 * t + 1);
                float h2 = __shfl_sync(0xffffffffu, hv, 2 * t + 8), h3 = __shfl_sync(0xffffffffu, hv, 2 * t + 9);
                const uint32_t b0 = pack_bf16(h0, h1), b1 = pack_bf16(h2, h3);
                float y[4][4];
#pragma unroll
                for (int j = 0; j < 4; j++) {
                    zero4(y[j]);
                    mma(y[j], S[8 + j], b0, b1);
                }
                float v0 = (t == 0) ? y[0][0] : (t == 1) ? y[1][2] : y[3][0];
                float v1 = (t == 0) ? y[0][2] : (t == 1) ? y[2][0] : y[3][2];
                float v2 = (t == 0) ? y[1][0] : (t == 1) ? y[2][2] : 0.f;
                STAMP(11 + layer * 14);
                if (layer == 0) {
                    if (own) red4(accw + eoff(1), v0, v1, v2, 1.f);
                    t_red = elapsed(0);
                } else if (own) {
                    float4 old = atom4(accp + eoff(3) + (g & 1) * 208, v0, v1, v2, 1.f);
                    if (b < 2) st_relaxed4(accw + eoff(0), 0.f, 0.f, 0.f, 0.f);
                    if (old.w == (float)(NFFN - 1)) {
                        const int c = 64 * w + 24 * t + g;
                        out[c] = __float2bfloat16(xo[0] + (old.x + v0));
                        out[c + 8] = __float2bfloat16(xo[1] + (old.y + v1));
                        if (t < 2) out[c + 16] = __float2bfloat16(xo[2] + (old.z + v2));
                    }
                }
            }
            STAMP(12 + layer * 14);
        }
    }
}

typedef CUresult (*EncodeFn)(CUtensorMap*, CUtensorMapDataType, cuuint32_t, void*, const cuuint64_t*, const cuuint64_t*,
                             const cuuint32_t*, const cuuint32_t*, CUtensorMapInterleave, CUtensorMapSwizzle,
                             CUtensorMapL2promotion, CUtensorMapFloatOOBfill);

void make_map(EncodeFn enc, CUtensorMap* m, const void* p, uint64_t cols, uint64_t rows, uint32_t bc, uint32_t br) {
    cuuint64_t gd[2] = {cols, rows};
    cuuint64_t gs[1] = {cols * 2};
    cuuint32_t bd[2] = {bc, br};
    cuuint32_t es[2] = {1, 1};
    enc(m, CU_TENSOR_MAP_DATA_TYPE_BFLOAT16, 2, const_cast<void*>(p), gd, gs, bd, es, CU_TENSOR_MAP_INTERLEAVE_NONE,
        bc == 64 ? CU_TENSOR_MAP_SWIZZLE_128B : CU_TENSOR_MAP_SWIZZLE_32B, CU_TENSOR_MAP_L2_PROMOTION_NONE,
        CU_TENSOR_MAP_FLOAT_OOB_FILL_NONE);
}

}

extern "C" void kernel_launch(void* const* d_in, const int* in_sizes, int n_in, void* d_out, int out_size) {
    (void)in_sizes; (void)n_in; (void)out_size;
    static EncodeFn enc = nullptr;
    static unsigned char* acc = nullptr;
    static MlRow* ml = nullptr;
    if (!enc) {
        void* p = nullptr;
        cudaGetSymbolAddress(&p, g_acc_raw);
        acc = reinterpret_cast<unsigned char*>((reinterpret_cast<uintptr_t>(p) + 32767) & ~(uintptr_t)32767);
        cudaGetSymbolAddress(&p, g_ml_buf);
        ml = reinterpret_cast<MlRow*>(p);
        cudaDriverEntryPointQueryResult qr;
        void* fn = nullptr;
        cudaGetDriverEntryPoint("cuTensorMapEncodeTiled", &fn, cudaEnableDefault, &qr);
        enc = (EncodeFn)fn;
        cudaFuncSetAttribute(fused_kernel, cudaFuncAttributeMaxDynamicSharedMemorySize, (int)SMEM_BYTES);
    }
    Maps mp;
    make_map(enc, &mp.wq, d_in[3], 4096, 512, 64, 256);
    make_map(enc, &mp.k, d_in[1], 128, 32 * 4096, 64, 64);
    make_map(enc, &mp.v, d_in[2], 128, 32 * 4096, 64, 64);
    make_map(enc, &mp.wo, d_in[4], 512, 4096, 64, 64);
    make_map(enc, &mp.w1, d_in[6], 1376, 512, 16, 256);
    make_map(enc, &mp.w3, d_in[7], 1376, 512, 16, 256);
    make_map(enc, &mp.w2, d_in[8], 512, 1376, 64, 16);
    fused_kernel<<<NCTA, NTHR, SMEM_BYTES>>>((const __nv_bfloat16*)d_in[0], (__nv_bfloat16*)d_out, acc, ml, mp);
}
```

```cpp
#include <cuda_runtime.h>
#include <cuda_bf16.h>
#include <cuda.h>
#include <stdint.h>

namespace {

constexpr int NCTA = 128;
constexpr int NTHR = 256;
constexpr int NFFN = 86;
#define NWO0 4
#define NWO1 9
#define PD2 500u
#define PD3 480u
#define PDN 700u
#define QNS 155
#define LEAD 5
#define FQ 44
#define F2Q 50
constexpr int SPIN_LIMIT = 1 << 20;

constexpr uint32_t OFF_WQ = 0;
constexpr uint32_t OFF_K = 65536;
constexpr uint32_t OFF_W13 = OFF_K + 5 * 8192;
constexpr uint32_t OFF_SX0 = OFF_K + 65536;
constexpr uint32_t OFF_WO5 = OFF_SX0 + 8192;
constexpr uint32_t OFF_V = OFF_WO5 + 24576;
constexpr uint32_t OFF_W2 = OFF_V;
constexpr uint32_t OFF_SX1 = OFF_V + 16384;
constexpr uint32_t OFF_FP = OFF_SX1 + 2048;
constexpr uint32_t OFF_FC = OFF_FP + 512;
constexpr uint32_t VS = 144;
constexpr uint32_t OFF_XS = OFF_V + 65536;
constexpr uint32_t OFF_PS = OFF_XS + 1152;
constexpr uint32_t OFF_QS = OFF_PS + 1152;
constexpr uint32_t OFF_OS = OFF_QS + 128;
constexpr uint32_t OFF_M = OFF_OS + 128;
constexpr uint32_t OFF_SQ = OFF_M + 32;
constexpr uint32_t OFF_BAR = OFF_SQ + 64;
constexpr uint32_t BS = 48;
constexpr uint32_t B_WQ = 0, B_K = 8, B_V = 16, B_WO = 24, B_F = 32, B_SX = 40;
constexpr uint32_t SMEM_BYTES = OFF_BAR + 8 * BS;
static_assert(SMEM_BYTES <= 232448, "smem");

struct Maps { CUtensorMap wq, k, v, wo, w1, w3, w2; };

typedef float2 MlRow[NCTA][16];
__device__ __align__(128) unsigned char g_acc_raw[65536];
__device__ __align__(128) float2 g_ml_buf[1][NCTA][16];
#define PROF_PARAM
#define STAMP(k) do {} while (0)

__device__ __forceinline__ void mbar_init(uint32_t a, int c) {
    asm volatile("mbarrier.init.shared::cta.b64 [%0], %1;" ::"r"(a), "r"(c) : "memory");
}
__device__ __forceinline__ void mbar_expect(uint32_t a, uint32_t bytes) {
    asm volatile("mbarrier.arrive.expect_tx.shared::cta.b64 _, [%0], %1;" ::"r"(a), "r"(bytes) : "memory");
}
__device__ __forceinline__ void mbar_wait(uint32_t a, uint32_t parity) {
    uint32_t ok;
    int n = 0;
    do {
        asm volatile("{\n.reg .pred p;\nmbarrier.try_wait.parity.shared::cta.b64 p, [%1], %2;\nselp.u32 %0, 1, 0, p;\n}"
                     : "=r"(ok) : "r"(a), "r"(parity) : "memory");
    } while (!ok && ++n < SPIN_LIMIT);
}
__device__ __forceinline__ bool mbar_test(uint32_t a) {
    uint32_t ok;
    asm volatile("{\n.reg .pred p;\nmbarrier.test_wait.parity.shared::cta.b64 p, [%1], 0;\nselp.u32 %0, 1, 0, p;\n}" : "=r"(ok) : "r"(a) : "memory");
    return ok;
}
__device__ __forceinline__ uint32_t gtime() {
    uint32_t c;
    asm volatile("mov.u32 %0, %%globaltimer_lo;" : "=r"(c) :: "memory");
    return __shfl_sync(0xffffffffu, c, 0);
}
__device__ __forceinline__ void tma2d(uint32_t dst, const CUtensorMap* m, int c0, int c1, uint32_t bar) {
    asm volatile("cp.async.bulk.tensor.2d.shared::cluster.global.mbarrier::complete_tx::bytes [%0], [%1, {%3, %4}], [%2];"
                 ::"r"(dst), "l"(m), "r"(bar), "r"(c0), "r"(c1) : "memory");
}
__device__ __forceinline__ void ldsm4(uint32_t* r, uint32_t a) {
    asm volatile("ldmatrix.sync.aligned.m8n8.x4.shared.b16 {%0,%1,%2,%3}, [%4];"
                 : "=r"(r[0]), "=r"(r[1]), "=r"(r[2]), "=r"(r[3]) : "r"(a) : "memory");
}
__device__ __forceinline__ void ldsm4t(uint32_t* r, uint32_t a) {
    asm volatile("ldmatrix.sync.aligned.m8n8.x4.trans.shared.b16 {%0,%1,%2,%3}, [%4];"
                 : "=r"(r[0]), "=r"(r[1]), "=r"(r[2]), "=r"(r[3]) : "r"(a) : "memory");
}
__device__ __forceinline__ void mma(float* c, const uint32_t* a, uint32_t b0, uint32_t b1) {
    asm("mma.sync.aligned.m16n8k16.row.col.f32.bf16.bf16.f32 {%0,%1,%2,%3},{%4,%5,%6,%7},{%8,%9},{%0,%1,%2,%3};"
        : "+f"(c[0]), "+f"(c[1]), "+f"(c[2]), "+f"(c[3])
        : "r"(a[0]), "r"(a[1]), "r"(a[2]), "r"(a[3]), "r"(b0), "r"(b1));
}
__device__ __forceinline__ uint4 lds128(uint32_t a) {
    uint4 v;
    asm volatile("ld.shared.v4.u32 {%0,%1,%2,%3}, [%4];" : "=r"(v.x), "=r"(v.y), "=r"(v.z), "=r"(v.w) : "r"(a) : "memory");
    return v;
}
__device__ __forceinline__ float4 lds128f(uint32_t a) {
    float4 v;
    asm volatile("ld.shared.v4.f32 {%0,%1,%2,%3}, [%4];" : "=f"(v.x), "=f"(v.y), "=f"(v.z), "=f"(v.w) : "r"(a) : "memory");
    return v;
}
__device__ __forceinline__ float2 lds64f(uint32_t a) {
    float2 v;
    asm volatile("ld.shared.v2.f32 {%0,%1}, [%2];" : "=f"(v.x), "=f"(v.y) : "r"(a) : "memory");
    return v;
}
__device__ __forceinline__ float lds32f(uint32_t a) {
    float v;
    asm volatile("ld.shared.f32 %0, [%1];" : "=f"(v) : "r"(a) : "memory");
    return v;
}
__device__ __forceinline__ void sts16(uint32_t a, uint32_t v) {
    asm volatile("st.shared.u16 [%0], %1;" ::"r"(a), "h"((unsigned short)v) : "memory");
}
__device__ __forceinline__ void sts32f(uint32_t a, float v) {
    asm volatile("st.shared.f32 [%0], %1;" ::"r"(a), "f"(v) : "memory");
}
__device__ __forceinline__ void cta_sync() { asm volatile("bar.sync 0;" ::: "memory"); }
__device__ __forceinline__ float ex2(float x) {
    float y;
    asm("ex2.approx.ftz.f32 %0, %1;" : "=f"(y) : "f"(x));
    return y;
}
__device__ __forceinline__ float rcp(float x) {
    float y;
    asm("rcp.approx.ftz.f32 %0, %1;" : "=f"(y) : "f"(x));
    return y;
}
__device__ __forceinline__ uint32_t pack_bf16(float lo, float hi) {
    uint32_t r;
    asm("cvt.rn.bf16x2.f32 %0, %1, %2;" : "=r"(r) : "f"(hi), "f"(lo));
    return r;
}
__device__ __forceinline__ float4 ld_relaxed4(const void* p) {
    float4 v;
    asm volatile("ld.relaxed.gpu.global.v4.f32 {%0,%1,%2,%3}, [%4];" : "=f"(v.x), "=f"(v.y), "=f"(v.z), "=f"(v.w) : "l"(p) : "memory");
    return v;
}
__device__ __forceinline__ float2 ld_relaxed2(const void* p) {
    float2 v;
    asm volatile("ld.relaxed.gpu.global.v2.f32 {%0,%1}, [%2];" : "=f"(v.x), "=f"(v.y) : "l"(p) : "memory");
    return v;
}
__device__ __forceinline__ void st_relaxed2(void* p, float x, float y) {
    asm volatile("st.relaxed.gpu.global.v2.f32 [%0], {%1,%2};" ::"l"(p), "f"(x), "f"(y) : "memory");
}
__device__ __forceinline__ void st_relaxed4(void* p, float x, float y, float z, float w) {
    asm volatile("st.relaxed.gpu.global.v4.f32 [%0], {%1,%2,%3,%4};" ::"l"(p), "f"(x), "f"(y), "f"(z), "f"(w) : "memory");
}
__device__ __forceinline__ void red4(void* p, float x, float y, float z, float w) {
    asm volatile("red.relaxed.gpu.global.add.v4.f32 [%0], {%1,%2,%3,%4};" ::"l"(p), "f"(x), "f"(y), "f"(z), "f"(w) : "memory");
}
__device__ __forceinline__ float4 atom4(void* p, float x, float y, float z, float w) {
    float4 v;
    asm volatile("atom.relaxed.gpu.global.add.v4.f32 {%0,%1,%2,%3}, [%4], {%5,%6,%7,%8};"
                 : "=f"(v.x), "=f"(v.y), "=f"(v.z), "=f"(v.w) : "l"(p), "f"(x), "f"(y), "f"(z), "f"(w) : "memory");
    return v;
}
__device__ __forceinline__ constexpr uint32_t eoff(int e) { return (uint32_t)((e & 1) * 128 + (e >> 1) * 512); }

constexpr uint32_t ONES = 0x3F803F80u;

__device__ __forceinline__ void mma_ab(float* c, uint32_t a0, uint32_t a1, uint32_t a2, uint32_t a3, uint32_t b0, uint32_t b1) {
    asm("mma.sync.aligned.m16n8k16.row.col.f32.bf16.bf16.f32 {%0,%1,%2,%3},{%4,%5,%6,%7},{%8,%9},{%0,%1,%2,%3};"
        : "+f"(c[0]), "+f"(c[1]), "+f"(c[2]), "+f"(c[3])
        : "r"(a0), "r"(a1), "r"(a2), "r"(a3), "r"(b0), "r"(b1));
}
__device__ __forceinline__ bool elect_one() {
    uint32_t p;
    asm volatile("{\n.reg .pred p;\nelect.sync _|p, 0xffffffff;\nselp.u32 %0, 1, 0, p;\n}" : "=r"(p));
    return p;
}
__device__ __forceinline__ float rsq(float x) {
    float y;
    asm("rsqrt.approx.ftz.f32 %0, %1;" : "=f"(y) : "f"(x));
    return y;
}
__device__ __forceinline__ uint32_t elapsed(uint32_t c0) {
    uint32_t c;
    asm volatile("mov.u32 %0, %%clock;" : "=r"(c) :: "memory");
    return __shfl_sync(0xffffffffu, c, 0) - c0 ;
}
__device__ __forceinline__ void zero4(float* c) { c[0] = c[1] = c[2] = c[3] = 0.f; }
__device__ __forceinline__ uint32_t pin(uint32_t v, int lane) { return __shfl_sync(0xffffffffu, v, lane); }

__device__ __forceinline__ void ln_partials(const uint4& u0, const uint4& u1, bool godd, float& s, float& q) {
    float c[4], d[4];
    zero4(c); zero4(d);
    mma_ab(c, u0.x, ONES, u0.y, ONES, u0.x, u0.y);
    mma_ab(d, u1.x, ONES, u1.y, ONES, u1.x, u1.y);
    mma_ab(c, u0.z, ONES, u0.w, ONES, u0.z, u0.w);
    mma_ab(d, u1.z, ONES, u1.w, ONES, u1.z, u1.w);
    s = (c[2] + d[2]) + (c[3] + d[3]);
    q = godd ? c[1] + d[1] : c[0] + d[0];
}
__device__ __forceinline__ void ln_finish(float s, float q, float& mean, float& rstd) {
    q += __shfl_xor_sync(0xffffffffu, q, 4);
    s += __shfl_xor_sync(0xffffffffu, s, 1);
    q += __shfl_xor_sync(0xffffffffu, q, 9);
    s += __shfl_xor_sync(0xffffffffu, s, 2);
    q += __shfl_xor_sync(0xffffffffu, q, 18);
    mean = s * (1.f / 512.f);
    q = __shfl_sync(0xffffffffu, q, 0);
    rstd = rsq(fmaxf(fmaf(-mean, mean, q * (1.f / 512.f)), 0.f) + 1e-5f);
}

#define FENCE() __syncwarp()
#define DEP2(x, d1, d2) ((x) | (((d1) | (d2)) & zr))
#define WO_FRAG(j) ldsm4t(Wf[j], (a_wo ^ (((j) & 3) << 5)) + ((j) >> 2) * 2048)

__global__ void __cluster_dims__(2, 1, 1) __launch_bounds__(NTHR, 1)
fused_kernel(const __nv_bfloat16* __restrict__ x_in, __nv_bfloat16* __restrict__ out, unsigned char* const acc_base, MlRow* const g_ml,
             PROF_PARAM const __grid_constant__ Maps mp) {
    extern __shared__ __align__(1024) unsigned char smem[];
    const uint32_t sb = (uint32_t)__cvta_generic_to_shared(smem);
    const int tid = threadIdx.x;
    const int b = blockIdx.x, r = b & 1, pr = (b >> 1) & 1, h = b >> 2;
    unsigned clk0;
    asm volatile("mov.u32 %0, %%clock;" : "=r"(clk0) :: "memory");
    if (tid == 0) {
        mbar_init(sb + OFF_BAR + B_WQ, 1);
        asm volatile("fence.mbarrier_init.release.cluster;" ::: "memory");
        mbar_expect(sb + OFF_BAR + B_WQ, 65536 + 1024);
        asm volatile("cp.async.bulk.shared::cluster.global.mbarrier::complete_tx::bytes [%0], [%1], 1024, [%2];"
                     ::"r"(sb + OFF_PS), "l"(x_in), "r"(sb + OFF_BAR + B_WQ) : "memory");
        tma2d(sb + OFF_WQ, &mp.wq, h * 128 + r * 64, 0, sb + OFF_BAR + B_WQ);
        tma2d(sb + OFF_WQ + 32768, &mp.wq, h * 128 + r * 64, 256, sb + OFF_BAR + B_WQ);
    }
    const uint32_t g0 = gtime();
    clk0 = __shfl_sync(0xffffffffu, clk0, 0);
    const int w = __shfl_sync(0xffffffffu, tid >> 5, 0), lane = tid & 31, g = lane >> 2, t = lane & 3;
    const bool ffn = b < NFFN;
    const uint32_t bars = sb + OFF_BAR + w * BS;
    if (elect_one()) {
        if (w >= 1 && w < 7) asm volatile("prefetch.tensormap [%0];" ::"l"(&mp.wq + w) : "memory");
        mbar_init(bars + B_K, 1); mbar_init(bars + B_V, 1); mbar_init(bars + B_WO, 1); mbar_init(bars + B_F, 1); mbar_init(bars + B_SX, 1);
        asm volatile("fence.mbarrier_init.release.cluster;" ::: "memory");
        mbar_expect(bars + B_SX, 256);
    }
    __syncwarp();
    STAMP(13);
    asm volatile("barrier.cluster.arrive.relaxed.aligned;" ::: "memory");

    unsigned char* const accp = acc_base + pin(w * 4096 + (g >> 1) * 1024 + ((g & 1) * 3 + (t < 3 ? t : 2)) * 16, lane);
    unsigned char* const accw = accp + r * 256;
    const bool own = t < 3;
    uint32_t zdep = 0;
    {
        const int z = tid - 32;
        unsigned char* zp;
        if (z < 16) zp = reinterpret_cast<unsigned char*>(&g_ml[0][b][0]) + (z >> 1) * 16 + 8 + (z & 1) * 4;
        else {
            const int i = b * 48 + (z - 16), e = 1 + (i >> 11), u = (i >> 5) & 63;
            zp = acc_base + (u >> 3) * 4096 + (u & 1) * 256 + ((u >> 1) & 3) * 1024 + (e & 1) * 128 + (e >> 1) * 512 + (i & 31) * 4;
        }
        asm volatile("{\n.reg .pred p;\nsetp.lt.u32 p, %2, 64;\n@p atom.relaxed.gpu.global.exch.b32 %0, [%1], 0;\n}"
                     : "+r"(zdep) : "l"(zp), "r"(z) : "memory");
    }

    const int mi = lane >> 3, li = lane & 7;
    const uint32_t wo_box = sb + (w < 5 ? OFF_K + w * 8192 : OFF_WO5 + (w - 5) * 8192);
    const uint32_t a_gemv = pin(sb + ((mi & 1) * 64 + (mi >> 1) * 8 + li) * 128 + ((w ^ li) << 4), lane);
    const uint32_t a_wo = pin(wo_box + ((mi >> 1) * 8 + li) * 128 + (((mi & 1) ^ li) << 4), lane);
    const uint32_t a_xst = pin(sb + OFF_XS + w * VS + (g >> 1) * 32 + (g & 1) * 2 + t * 12, lane);
    const uint32_t a_pst = pin(sb + OFF_PS + w * VS + (g >> 1) * 32 + (g & 1) * 2 + t * 8, lane);
    const uint32_t a_row = pin(sb + g * VS + t * 32, lane);
    const uint32_t a_qo = pin(sb + (g >> 1) * 32 + w * 4 + (g & 1) * 2, lane);
    const uint32_t a_t32 = pin(sb + t * 32, lane);
    const uint32_t a_sx = pin(sb + tid * 8, lane);
    uint32_t peer_sx, peer_bar;
    asm volatile("mapa.shared::cluster.u32 %0, %1, %2;" : "=r"(peer_sx) : "r"(a_sx), "r"(r ^ 1));
    asm volatile("mapa.shared::cluster.u32 %0, %1, %2;" : "=r"(peer_bar) : "r"(bars + B_SX), "r"(r ^ 1));
    const float2* const mlp = &g_ml[0][0][0] + pin((b ^ 2) * 16 + 2 * g, lane);
    float2* const mlo = &g_ml[0][0][0] + pin(b * 16 + 2 * g, lane);
    const uint32_t a_mg = pin(sb + OFF_M + g * 4, lane), a_mt = pin(sb + OFF_M + t * 8, lane), a_sb = pin(sb, lane), a_bsx = pin(bars + B_SX, lane);
    const uint32_t zr = pin(tid >> 20, lane);

    int todo = 1, vi = 0;
    uint32_t due = (uint32_t)((8 + 2 * w - LEAD) * QNS);
    const int kr = h * 4096 + 3072 + pr * 512;
    auto issue = [&]() {
        const bool el = elect_one();
        if (todo == 1) {
            if (el) { mbar_expect(bars + B_K, 8192); tma2d(sb + OFF_K + w * 8192, &mp.k, r * 64, kr + w * 64, bars + B_K); }
            todo = 0;
        } else if (todo == 2) {
            if (el) {
                const uint32_t bar = sb + OFF_BAR + (vi >> 1) * BS + B_V;
                if (!(vi & 1)) mbar_expect(bar, 16384);
                tma2d(sb + OFF_V + vi * 8192, &mp.v, r * 64, kr + vi * 64, bar);
            }
            vi++; due += 2 * QNS;
            if (vi == 8) todo = 0;
        } else if (todo == 3) {
            if (el) { mbar_expect(bars + B_WO, 8192); tma2d(wo_box, &mp.wo, w * 64, h * 128 + r * 64, bars + B_WO); }
            todo = (ffn && w < 4) ? 4 : 0;
            due = (uint32_t)((FQ - LEAD) * QNS + w * (4 * QNS / 3));
        } else if (todo == 4) {
            if (el) { mbar_expect(bars + B_F, 8192); tma2d(sb + OFF_W13 + w * 8192, (w & 1) ? &mp.w3 : &mp.w1, b * 16, (w >> 1) * 256, bars + B_F); }
            todo = 0;
        } else {
            if (el) {
                mbar_expect(bars + B_F, 4096);
                tma2d(sb + OFF_W2 + (w - 4) * 4096, &mp.w2, (w - 4) * 128, b * 16, bars + B_F);
                tma2d(sb + OFF_W2 + (w - 4) * 4096 + 2048, &mp.w2, (w - 4) * 128 + 64, b * 16, bars + B_F);
            }
            todo = 0;
        }
        __syncwarp();
    };
    auto gated_wait = [&](uint32_t bar) {
        int n = SPIN_LIMIT;
        while (todo) {
            if (gtime() - g0 >= due) issue();
            if (mbar_test(bar) || --n < 0) return;
        }
        mbar_wait(bar, 0);
    };
    uint32_t Kf[16][4], Vf[16][4], S[16][4], Wf[16][4];
    float cs_q = 0.f, cs_g = 0.f, cs_u = 0.f;
    STAMP(0);
    asm volatile("barrier.cluster.wait.acquire.aligned;" ::: "memory");
    gated_wait(sb + OFF_BAR + B_WQ);
    if (todo) issue();
    STAMP(14);
    float xo[3];
#pragma unroll
    for (int i = 0; i < 3; i++) {
        uint32_t xr;
        asm volatile("ld.shared.u16 %0, [%1];" : "=r"(xr) : "r"(sb + OFF_PS + (64 * w + 8 * ((3 * t + i) & 7) + g) * 2) : "memory");
        xo[i] = __uint_as_float(xr << 16);
    }

    uint32_t p01 = 0, p2 = 0;
    auto put_x = [&](float vx, float vy, float vz) {
        p01 = pack_bf16(xo[0] + vx, xo[1] + vy);
        p2 = pack_bf16(xo[2] + vz, 0.f);
        if (own) { sts16(a_xst, p01); sts16(a_xst + 4, p01 >> 16); }
        if (t < 2) sts16(a_xst + 8, p2);
    };
    auto commit_x = [&]() {
        cta_sync();
        xo[0] = __uint_as_float(p01 << 16); xo[1] = __uint_as_float(p01 & 0xffff0000u); xo[2] = __uint_as_float(p2 << 16);
    };
    uint32_t t_red = 0;
    auto exchange_wait = [&](const unsigned char* p, float target, uint32_t delay) {
        int n = SPIN_LIMIT;
        if (delay) while (elapsed(t_red) < delay) {}
        bool more;
        do {
            const float4 v = ld_relaxed4(p), v2 = ld_relaxed4(p + 256);
            --n;
            more = __any_sync(0xffffffffu, v.w + v2.w != target && n > 0);
            put_x(v.x + v2.x, v.y + v2.y, v.z + v2.z);
        } while (more);
        commit_x();
    };

#pragma unroll
    for (int layer = 0; layer < 2; layer++) {
#pragma unroll
        for (int j = 0; j < 16; j++) ldsm4t(S[j], a_gemv + OFF_WQ + ((j >> 2) * 128 + (j & 3) * 16) * 128);
        if (layer == 0) {
            float c0[4], c1[4];
            zero4(c0); zero4(c1);
#pragma unroll
            for (int j = 0; j < 8; j++) { mma(c0, S[2 * j], ONES, ONES); mma(c1, S[2 * j + 1], ONES, ONES); }
            cs_q = ((c0[0] + c0[3]) + (c1[0] + c1[3])) * (1.f / 512.f);
            put_x(0.f, 0.f, 0.f);
            commit_x();
            if (b < 2 && own) red4(accw, 0.5f * xo[0], 0.5f * xo[1], t < 2 ? 0.5f * xo[2] : 0.f, 1.f);
            xo[0] = xo[1] = xo[2] = 0.f;
        } else {
            if (!ffn) { exchange_wait(accp + eoff(0), (float)(NCTA + 2), 0); t_red = elapsed(0) + PDN; if (PDN) while ((int)elapsed(t_red) < 0) {} }
            exchange_wait(accp + eoff(1), (float)NFFN, PD2);
        }
        STAMP(1 + layer * 14);
        float ls, lq;
        {
            uint4 u0 = lds128(a_row + OFF_XS), u1 = lds128(a_row + OFF_XS + 16);
            float acc[4][4];
#pragma unroll
            for (int a = 0; a < 4; a++) { zero4(acc[a]); mma(acc[a], S[a * 4 + 0], u0.x, u0.y); }
            ln_partials(u0, u1, g & 1, ls, lq);
#pragma unroll
            for (int a = 0; a < 4; a++) mma(acc[a], S[a * 4 + 1], u0.z, u0.w);
#pragma unroll
            for (int a = 0; a < 4; a++) mma(acc[a], S[a * 4 + 2], u1.x, u1.y);
#pragma unroll
            for (int a = 0; a < 4; a++) mma(acc[a], S[a * 4 + 3], u1.z, u1.w);
            float e0 = (t & 2) ? ((t & 1) ? acc[3][0] : acc[2][0]) : ((t & 1) ? acc[1][0] : acc[0][0]);
            float e1 = (t & 2) ? ((t & 1) ? acc[3][3] : acc[2][3]) : ((t & 1) ? acc[1][3] : acc[0][3]);
            float q = fmaf(-ls, cs_q, e0) + e1;
            q += __shfl_xor_sync(0xffffffffu, q, 1);
            q += __shfl_xor_sync(0xffffffffu, q, 2);
            if (t == 0) sts16(a_qo + OFF_QS, pack_bf16(q, 0.f));
        }
        STAMP(2 + layer * 14);
        cta_sync();
        if (layer == 0) {
            if (w == 7) { todo = 2; due = (uint32_t)((24 - LEAD) * QNS); }
            gated_wait(bars + B_K);
            while (todo) issue();
#pragma unroll
            for (int j = 0; j < 16; j++)
                ldsm4(Kf[j], sb + OFF_K + w * 8192 + ((j >> 2) * 16 + (mi & 1) * 8 + li) * 128 + ((((j & 3) * 2 + (mi >> 1)) ^ li) << 4));
        }
        float s0, s1, scl;
        {
            uint4 q0 = lds128(a_t32 + OFF_QS), q1 = lds128(a_t32 + OFF_QS + 16);
            float sc[4][4];
#pragma unroll
            for (int j = 0; j < 4; j++) { zero4(sc[j]); mma(sc[j], Kf[j * 4 + 0], q0.x, q0.y); }
#pragma unroll
            for (int j = 0; j < 4; j++) mma(sc[j], Kf[j * 4 + 1], q0.z, q0.w);
#pragma unroll
            for (int j = 0; j < 4; j++) mma(sc[j], Kf[j * 4 + 2], q1.x, q1.y);
#pragma unroll
            for (int j = 0; j < 4; j++) mma(sc[j], Kf[j * 4 + 3], q1.z, q1.w);
            float mean, rstd;
            ln_finish(ls, lq, mean, rstd);
            scl = rstd * (0.08838834764831845f * 1.4426950408889634f);
            s0 = (t & 2) ? ((t & 1) ? sc[3][0] : sc[2][0]) : ((t & 1) ? sc[1][0] : sc[0][0]);
            s1 = (t & 2) ? ((t & 1) ? sc[3][2] : sc[2][2]) : ((t & 1) ? sc[1][2] : sc[0][2]);
            asm volatile("st.async.weak.shared::cluster.mbarrier::complete_tx::bytes.v2.f32 [%0], {%1,%2}, [%3];"
                         ::"r"(peer_sx + (layer ? OFF_SX1 : OFF_SX0)), "f"(s0), "f"(s1), "r"(peer_bar) : "memory");
            FENCE();
            if (layer == 1) {
#pragma unroll
                for (int j = NWO0; j < NWO1; j++) WO_FRAG(j);
            }
        }
        STAMP(3 + layer * 14);
        s0 *= scl; s1 *= scl;
        mbar_wait(a_bsx, layer);
        {
            float2 o2 = lds64f(a_sx + (layer ? OFF_SX1 : OFF_SX0));
            s0 = fmaf(o2.x, scl, s0);
            s1 = fmaf(o2.y, scl, s1);
            int mi_ = __float_as_int(fmaxf(fmaxf(s0, s1), -3.0e38f));
            mi_ ^= (mi_ >> 31) & 0x7fffffff;
            mi_ = __reduce_max_sync(0xffffffffu, mi_);
            mi_ ^= (mi_ >> 31) & 0x7fffffff;
            const float mw = __int_as_float(mi_);
            uint32_t pp = pack_bf16(ex2(s0 - mw), ex2(s1 - mw));
            sts16(a_pst, pp);
            sts16(a_pst + 4, pp >> 16);
            if (lane == 0) sts32f(a_qo + OFF_M, mw);
        }
        STAMP(4 + layer * 14);
        cta_sync();
        float M, tot;
        float2 rem, rem2;
        {
            uint4 u0 = lds128(a_row + OFF_PS), u1 = lds128(a_row + OFF_PS + 16);
            float mg = lds32f(a_mg);
            FENCE();
            float4 m0 = lds128f(a_sb + OFF_M), m1 = lds128f(a_sb + OFF_M + 16);
            float2 mt = lds64f(a_mt);
            if (w == 0) {
                float c[4], d[4];
                zero4(c); zero4(d);
                mma_ab(c, u0.x, u0.y, u0.z, u0.w, ONES, ONES);
                mma_ab(d, u1.x, u1.y, u1.z, u1.w, ONES, ONES);
                const float l0 = (c[1] + c[3]) + (d[1] + d[3]);
                if (t == 0) st_relaxed2(mlo + layer, mg, __uint_as_float(__float_as_uint(l0) | 0x80000000u));
                __syncwarp();
            }
            float acc[4][4];
            if (layer == 0) {
                if (lane == 0) mbar_expect(bars + B_SX, 256);
                asm volatile("{\n.reg .pred p;\nsetp.eq.u32 p, %0, 0x7fd3a5c1;\n@p nanosleep.u32 1;\n}" ::"r"(zdep) : "memory");
                todo = 3; due = (uint32_t)((40 - LEAD) * QNS + w * (QNS / 2));
#pragma unroll
                for (int a = 0; a < 4; a++) {
                    if (a == 1) rem = ld_relaxed2(mlp);
                    gated_wait(sb + OFF_BAR + a * BS + B_V);
                    if (a == 3) STAMP(27);
#pragma unroll
                    for (int j = 0; j < 4; j++) ldsm4t(Vf[a * 4 + j], a_gemv + OFF_V + (a * 128 + j * 16) * 128);
                    zero4(acc[a]);
                    mma(acc[a], Vf[a * 4 + 0], u0.x, u0.y);
                    mma(acc[a], Vf[a * 4 + 1], u0.z, u0.w);
                    mma(acc[a], Vf[a * 4 + 2], u1.x, u1.y);
                    mma(acc[a], Vf[a * 4 + 3], u1.z, u1.w);
                }
            } else {
#pragma unroll
                for (int a = 0; a < 4; a++) { zero4(acc[a]); mma(acc[a], Vf[a * 4 + 0], u0.x, u0.y); }
                WO_FRAG(NWO1); WO_FRAG(NWO1 + 1); WO_FRAG(NWO1 + 2); WO_FRAG(NWO1 + 3);
                const uint32_t d0 = __float_as_uint(acc[3][1]);
                m0.x = __uint_as_float(DEP2(__float_as_uint(m0.x), d0, d0)); m0.z = __uint_as_float(DEP2(__float_as_uint(m0.z), d0, d0));
                m1.x = __uint_as_float(DEP2(__float_as_uint(m1.x), d0, d0)); m1.z = __uint_as_float(DEP2(__float_as_uint(m1.z), d0, d0));
#pragma unroll
                for (int a = 0; a < 4; a++) mma(acc[a], Vf[a * 4 + 1], u0.z, u0.w);
#pragma unroll
                for (int a = 0; a < 4; a++) mma(acc[a], Vf[a * 4 + 2], u1.x, u1.y);
                uint32_t bz = DEP2(u1.z, Wf[NWO1][0], Wf[NWO1 + 1][0]), bw = DEP2(u1.w, Wf[NWO1 + 2][0], Wf[NWO1 + 3][0]);
#pragma unroll
                for (int a = 0; a < 4; a++) mma(acc[a], Vf[a * 4 + 3], bz, bw);
            }
            M = fmaxf(fmaxf(fmaxf(m0.x, m0.y), fmaxf(m0.z, m0.w)), fmaxf(fmaxf(m1.x, m1.y), fmaxf(m1.z, m1.w)));
            {
                float c[4];
                zero4(c);
                mma_ab(c, u0.x, u0.y, u0.z, u0.w, ONES, ONES);
                mma_ab(c, u1.x, u1.y, u1.z, u1.w, ONES, ONES);
                tot = (c[0] + c[2]) * ex2(mg - M);
            }
            const float f0 = ex2(mt.x - M), f1 = ex2(mt.y - M);
            float e0 = (t & 2) ? ((t & 1) ? acc[3][0] : acc[2][0]) : ((t & 1) ? acc[1][0] : acc[0][0]);
            float e1 = (t & 2) ? ((t & 1) ? acc[3][3] : acc[2][3]) : ((t & 1) ? acc[1][3] : acc[0][3]);
            float o = fmaf(f0, e0, f1 * e1);
            if (layer == 1) { FENCE(); rem = ld_relaxed2(mlp + 1); }
            o += __shfl_xor_sync(0xffffffffu, o, 1);
            o += __shfl_xor_sync(0xffffffffu, o, 2);
            if (t == 0) sts16(a_qo + OFF_OS, pack_bf16(o, 0.f));
        }
        STAMP(5 + layer * 14);
        cta_sync();
        if (layer == 0) {
            if (todo == 3) issue();
            if (w >= 4 && ffn) { todo = 5; due = (uint32_t)((F2Q - LEAD) * QNS); }
            gated_wait(bars + B_WO);
            STAMP(28);
#pragma unroll
            for (int j = 0; j < NWO1 + 4; j++) WO_FRAG(j);
        }
        {
            uint4 o0 = lds128(a_t32 + OFF_OS), o1 = lds128(a_t32 + OFF_OS + 16);
#pragma unroll
            for (int j = NWO1 + 4; j < 16; j++) WO_FRAG(j);
            if (layer == 1) rem2 = ld_relaxed2(mlp + 1); else rem2 = rem;
            FENCE();
            float y[4][4];
#pragma unroll
            for (int j = 0; j < 4; j++) { zero4(y[j]); mma(y[j], Wf[j], o0.x, o0.y); }
#pragma unroll
            for (int j = 0; j < 4; j++) mma(y[j], Wf[4 + j], o0.z, o0.w);
#pragma unroll
            for (int j = 0; j < 4; j++) mma(y[j], Wf[8 + j], o1.x, o1.y);
#pragma unroll
            for (int j = 0; j < 4; j++) mma(y[j], Wf[12 + j], o1.z, o1.w);
            FENCE();
            STAMP(6 + layer * 14);
            if (!__all_sync(0xffffffffu, __float_as_uint(rem.y) != 0u)) {
                rem = rem2;
                int n = 0;
                while (!__all_sync(0xffffffffu, __float_as_uint(rem.y) != 0u) && ++n < SPIN_LIMIT) rem = ld_relaxed2(mlp + layer);
            }
            tot = fmaf(-rem.y, ex2(rem.x - M), tot);
            tot += __shfl_xor_sync(0xffffffffu, tot, 4);
            tot += __shfl_xor_sync(0xffffffffu, tot, 8);
            tot += __shfl_xor_sync(0xffffffffu, tot, 16);
            const float inv = rcp(tot);
            float v0 = (t == 0) ? y[0][0] : (t == 1) ? y[1][2] : y[3][0];
            float v1 = (t == 0) ? y[0][2] : (t == 1) ? y[2][0] : y[3][2];
            float v2 = (t == 0) ? y[1][0] : (t == 1) ? y[2][2] : 0.f;
            if (own) red4(accw + layer * eoff(2), v0 * inv, v1 * inv, v2 * inv, 1.f);
            t_red = elapsed(0);
            if (layer == 1 && w == 0 && t == 0) st_relaxed2(mlo, 0.f, 0.f);
        }
        STAMP(7 + layer * 14);

        if (ffn) {
            const uint32_t a_fst = pin(sb + OFF_FP + (w >> 2) * 256 + ((w & 1) * 8 + g) * 16 + ((w >> 1) & 1) * 8, lane);
            const bool fst = t == (w >> 1);
            const uint32_t a_frd = pin(sb + OFF_FP + (lane & 15) * 16, lane);
            const uint32_t a_w2 = sb + OFF_W2 + w * 2048 + ((mi >> 1) * 8 + li) * 128 + (((mi & 1) ^ li) << 4);
            if (layer == 0) {
                while (todo) if (gtime() - g0 >= due) issue();
            }
            const uint32_t a_w13 = sb + OFF_W13 + (w >> 2) * 16384 + (mi & 1) * 8192 + (((w >> 1) & 1) * 128 + (mi >> 1) * 8 + li) * 32 + (((w & 1) ^ (li >> 2)) << 4);
            auto stage_w13 = [&]() {
#pragma unroll
                for (int j = 0; j < 8; j++) ldsm4t(S[j], a_w13 + j * 16 * 32);
                if (layer == 0) {
                    float c0[4], c1[4];
                    zero4(c0); zero4(c1);
#pragma unroll
                    for (int j = 0; j < 4; j++) { mma(c0, S[2 * j], ONES, ONES); mma(c1, S[2 * j + 1], ONES, ONES); }
                    if (t == 0) asm volatile("st.shared.v2.f32 [%0], {%1,%2};" ::"r"(a_fst + (OFF_FC - OFF_FP)), "f"(c0[0] + c1[0]), "f"(c0[2] + c1[2]) : "memory");
                }
            };
            if (layer == 0) {
                const uint32_t bw1 = sb + OFF_BAR + (w >> 2) * 2 * BS + B_F;
                bool staged = false, more;
                int n = SPIN_LIMIT;
                do {
                    const float4 v = ld_relaxed4(accp), v2 = ld_relaxed4(accp + 256);
                    if (!staged && mbar_test(bw1) && mbar_test(bw1 + BS)) { stage_w13(); staged = true; }
                    --n;
                    more = __any_sync(0xffffffffu, v.w + v2.w != (float)(NCTA + 2) && n > 0);
                    put_x(v.x + v2.x, v.y + v2.y, v.z + v2.z);
                } while (more);
                STAMP(8);
                if (!staged) { mbar_wait(bw1, 0); mbar_wait(bw1 + BS, 0); STAMP(29); stage_w13(); }
                commit_x();
            } else {
                stage_w13();
#pragma unroll
                for (int j = 0; j < 4; j++) ldsm4t(S[8 + j], a_w2 ^ (j << 5));
                STAMP(8 + layer * 14);
                exchange_wait(accp + eoff(2), (float)NCTA, PD3);
            }
            STAMP(9 + layer * 14);
            {
                uint4 u0 = lds128(a_row + OFF_XS), u1 = lds128(a_row + OFF_XS + 16);
                if (layer == 0) {
                    float4 p0 = lds128f(a_frd + (OFF_FC - OFF_FP)), p1 = lds128f(a_frd + (OFF_FC - OFF_FP) + 256);
                    cs_g = (p0.x + p0.z) + (p1.x + p1.z);
                    cs_u = (p0.y + p0.w) + (p1.y + p1.w);
                }
                {
                    const uint32_t z0 = own ? p01 : 0u, z1 = t < 2 ? p2 : 0u;
                    float c[4];
                    zero4(c);
                    mma_ab(c, z0, ONES, z1, ONES, z0, z1);
                    float s_ = c[2] + c[3], q_ = (g & 1) ? c[1] : c[0];
                    q_ += __shfl_xor_sync(0xffffffffu, q_, 4);
                    s_ += __shfl_xor_sync(0xffffffffu, s_, 1);
                    q_ += __shfl_xor_sync(0xffffffffu, q_, 9);
                    s_ += __shfl_xor_sync(0xffffffffu, s_, 2);
                    q_ += __shfl_xor_sync(0xffffffffu, q_, 18);
                    if (lane == 0) { sts32f(a_qo + OFF_SQ, s_); sts32f(a_qo + OFF_SQ + 32, q_); }
                }
                float acc[4][4];
                zero4(acc[0]); zero4(acc[1]); zero4(acc[2]); zero4(acc[3]);
                mma(acc[0], S[0], u0.x, u0.y); mma(acc[1], S[4], u0.x, u0.y); mma(acc[2], S[2], u1.x, u1.y); mma(acc[3], S[6], u1.x, u1.y);
                mma(acc[0], S[1], u0.z, u0.w); mma(acc[1], S[5], u0.z, u0.w); mma(acc[2], S[3], u1.z, u1.w); mma(acc[3], S[7], u1.z, u1.w);
                if (fst) asm volatile("st.shared.v2.f32 [%0], {%1,%2};" ::"r"(a_fst), "f"((acc[0][0] + acc[2][0]) + (acc[1][1] + acc[3][1])),
                                      "f"((acc[0][2] + acc[2][2]) + (acc[1][3] + acc[3][3])) : "memory");
            }
            STAMP(10 + layer * 14);
            cta_sync();
            {
                const float4 s0 = lds128f(a_sb + OFF_SQ), s1 = lds128f(a_sb + OFF_SQ + 16), q0 = lds128f(a_sb + OFF_SQ + 32), q1 = lds128f(a_sb + OFF_SQ + 48);
                float4 p0 = lds128f(a_frd), p1 = lds128f(a_frd + 256);
                const float mean2 = (((s0.x + s0.y) + (s0.z + s0.w)) + ((s1.x + s1.y) + (s1.z + s1.w))) * (1.f / 512.f);
                const float ssq = ((q0.x + q0.y) + (q0.z + q0.w)) + ((q1.x + q1.y) + (q1.z + q1.w));
                const float rstd2 = rsq(fmaxf(fmaf(-mean2, mean2, fmaf(ssq, 1.f / 512.f, 1e-5f)), 1e-5f));
                if (layer == 0) {
                    mbar_wait(sb + OFF_BAR + (4 + (w >> 1)) * BS + B_F, 0);
#pragma unroll
                    for (int j = 0; j < 4; j++) ldsm4t(S[8 + j], a_w2 ^ (j << 5));
                }
                float gate = rstd2 * (fmaf(-mean2, cs_g, p0.x + p0.z) + (p1.x + p1.z));
                float up = rstd2 * (fmaf(-mean2, cs_u, p0.y + p0.w) + (p1.y + p1.w));
                float hv = gate * up * rcp(1.f + ex2(-1.4426950408889634f * gate));
                float h0 = __shfl_sync(0xffffffffu, hv, 2 * t), h1 = __shfl_sync(0xffffffffu, hv, 2 * t + 1);
                float h2 = __shfl_sync(0xffffffffu, hv, 2 * t + 8), h3 = __shfl_sync(0xffffffffu, hv, 2 * t + 9);
                const uint32_t b0 = pack_bf16(h0, h1), b1 = pack_bf16(h2, h3);
                float y[4][4];
#pragma unroll
                for (int j = 0; j < 4; j++) {
                    zero4(y[j]);
                    mma(y[j], S[8 + j], b0, b1);
                }
                float v0 = (t == 0) ? y[0][0] : (t == 1) ? y[1][2] : y[3][0];
                float v1 = (t == 0) ? y[0][2] : (t == 1) ? y[2][0] : y[3][2];
                float v2 = (t == 0) ? y[1][0] : (t == 1) ? y[2][2] : 0.f;
                STAMP(11 + layer * 14);
                if (layer == 0) {
                    if (own) red4(accw + eoff(1), v0, v1, v2, 1.f);
                    t_red = elapsed(0);
                } else if (own) {
                    float4 old = atom4(accp + eoff(3) + (g & 1) * 208, v0, v1, v2, 1.f);
                    if (b < 2) st_relaxed4(accw + eoff(0), 0.f, 0.f, 0.f, 0.f);
                    if (old.w == (float)(NFFN - 1)) {
                        const int c = 64 * w + 24 * t + g;
                        out[c] = __float2bfloat16(xo[0] + (old.x + v0));
                        out[c + 8] = __float2bfloat16(xo[1] + (old.y + v1));
                        if (t < 2) out[c + 16] = __float2bfloat16(xo[2] + (old.z + v2));
                    }
                }
            }
            STAMP(12 + layer * 14);
        }
    }
}

typedef CUresult (*EncodeFn)(CUtensorMap*, CUtensorMapDataType, cuuint32_t, void*, const cuuint64_t*, const cuuint64_t*,
                             const cuuint32_t*, const cuuint32_t*, CUtensorMapInterleave, CUtensorMapSwizzle,
                             CUtensorMapL2promotion, CUtensorMapFloatOOBfill);

void make_map(EncodeFn enc, CUtensorMap* m, const void* p, uint64_t cols, uint64_t rows, uint32_t bc, uint32_t br) {
    cuuint64_t gd[2] = {cols, rows};
    cuuint64_t gs[1] = {cols * 2};
    cuuint32_t bd[2] = {bc, br};
    cuuint32_t es[2] = {1, 1};
    enc(m, CU_TENSOR_MAP_DATA_TYPE_BFLOAT16, 2, const_cast<void*>(p), gd, gs, bd, es, CU_TENSOR_MAP_INTERLEAVE_NONE,
        bc == 64 ? CU_TENSOR_MAP_SWIZZLE_128B : CU_TENSOR_MAP_SWIZZLE_32B, CU_TENSOR_MAP_L2_PROMOTION_NONE,
        CU_TENSOR_MAP_FLOAT_OOB_FILL_NONE);
}

}

extern "C" void kernel_launch(void* const* d_in, const int* in_sizes, int n_in, void* d_out, int out_size) {
    (void)in_sizes; (void)n_in; (void)out_size;
    static EncodeFn enc = nullptr;
    static unsigned char* acc = nullptr;
    static MlRow* ml = nullptr;
    if (!enc) {
        void* p = nullptr;
        cudaGetSymbolAddress(&p, g_acc_raw);
        acc = reinterpret_cast<unsigned char*>((reinterpret_cast<uintptr_t>(p) + 32767) & ~(uintptr_t)32767);
        cudaGetSymbolAddress(&p, g_ml_buf);
        ml = reinterpret_cast<MlRow*>(p);
        cudaDriverEntryPointQueryResult qr;
        void* fn = nullptr;
        cudaGetDriverEntryPoint("cuTensorMapEncodeTiled", &fn, cudaEnableDefault, &qr);
        enc = (EncodeFn)fn;
        cudaFuncSetAttribute(fused_kernel, cudaFuncAttributeMaxDynamicSharedMemorySize, (int)SMEM_BYTES);
    }
    Maps mp;
    make_map(enc, &mp.wq, d_in[3], 4096, 512, 64, 256);
    make_map(enc, &mp.k, d_in[1], 128, 32 * 4096, 64, 64);
    make_map(enc, &mp.v, d_in[2], 128, 32 * 4096, 64, 64);
    make_map(enc, &mp.wo, d_in[4], 512, 4096, 64, 64);
    make_map(enc, &mp.w1, d_in[6], 1376, 512, 16, 256);
    make_map(enc, &mp.w3, d_in[7], 1376, 512, 16, 256);
    make_map(enc, &mp.w2, d_in[8], 512, 1376, 64, 16);
    fused_kernel<<<NCTA, NTHR, SMEM_BYTES>>>((const __nv_bfloat16*)d_in[0], (__nv_bfloat16*)d_out, acc, ml, mp);
}
```

```cpp
#include <cuda_runtime.h>
#include <cuda_bf16.h>
#include <cuda.h>
#include <stdint.h>

namespace {

constexpr int NCTA = 128;
constexpr int NTHR = 256;
constexpr int NFFN = 86;
#define NWO0 3
#define NWO1 8
#define PD2 500u
#define PD3 480u
#define PDN 700u
#define QNS 155
#define LEAD 5
#define FQ 46
#define F2Q 62
#define WOQ 40
#define P1NS 8800u
constexpr int SPIN_LIMIT = 1 << 20;

constexpr uint32_t OFF_WQ = 0;
constexpr uint32_t OFF_K = 65536;
constexpr uint32_t OFF_W13 = OFF_K + 5 * 8192;
constexpr uint32_t OFF_SX0 = OFF_K + 65536;
constexpr uint32_t OFF_WO5 = OFF_SX0 + 8192;
constexpr uint32_t OFF_V = OFF_WO5 + 24576;
constexpr uint32_t OFF_W2 = OFF_V;
constexpr uint32_t OFF_SX1 = OFF_V + 16384;
constexpr uint32_t OFF_FP = OFF_SX1 + 2048;
constexpr uint32_t OFF_FC = OFF_FP + 512;
constexpr uint32_t VS = 144;
constexpr uint32_t OFF_XS = OFF_V + 65536;
constexpr uint32_t OFF_PS = OFF_XS + 1152;
constexpr uint32_t OFF_QS = OFF_PS + 1152;
constexpr uint32_t OFF_OS = OFF_QS + 128;
constexpr uint32_t OFF_M = OFF_OS + 128;
constexpr uint32_t OFF_SQ = OFF_M + 32;
constexpr uint32_t OFF_BAR = OFF_SQ + 64;
constexpr uint32_t BS = 48;
constexpr uint32_t B_WQ = 0, B_K = 8, B_V = 16, B_WO = 24, B_F = 32, B_SX = 40;
constexpr uint32_t SMEM_BYTES = OFF_BAR + 8 * BS;
static_assert(SMEM_BYTES <= 232448, "smem");

struct Maps { CUtensorMap wq, k, v, wo, w1, w3, w2; };

typedef float2 MlRow[NCTA][16];
__device__ __align__(128) unsigned char g_acc_raw[65536];
__device__ __align__(128) float2 g_ml_buf[1][NCTA][16];
#define PROF_PARAM
#define STAMP(k) do {} while (0)

__device__ __forceinline__ void mbar_init(uint32_t a, int c) {
    asm volatile("mbarrier.init.shared::cta.b64 [%0], %1;" ::"r"(a), "r"(c) : "memory");
}
__device__ __forceinline__ void mbar_expect(uint32_t a, uint32_t bytes) {
    asm volatile("mbarrier.arrive.expect_tx.shared::cta.b64 _, [%0], %1;" ::"r"(a), "r"(bytes) : "memory");
}
__device__ __forceinline__ void mbar_wait(uint32_t a, uint32_t parity) {
    uint32_t ok;
    int n = 0;
    do {
        asm volatile("{\n.reg .pred p;\nmbarrier.try_wait.parity.shared::cta.b64 p, [%1], %2;\nselp.u32 %0, 1, 0, p;\n}"
                     : "=r"(ok) : "r"(a), "r"(parity) : "memory");
    } while (!ok && ++n < SPIN_LIMIT);
}
__device__ __forceinline__ bool mbar_test(uint32_t a) {
    uint32_t ok;
    asm volatile("{\n.reg .pred p;\nmbarrier.test_wait.parity.shared::cta.b64 p, [%1], 0;\nselp.u32 %0, 1, 0, p;\n}" : "=r"(ok) : "r"(a) : "memory");
    return ok;
}
__device__ __forceinline__ uint32_t gtime() {
    uint32_t c;
    asm volatile("mov.u32 %0, %%globaltimer_lo;" : "=r"(c) :: "memory");
    return __shfl_sync(0xffffffffu, c, 0);
}
__device__ __forceinline__ void tma2d(uint32_t dst, const CUtensorMap* m, int c0, int c1, uint32_t bar) {
    asm volatile("cp.async.bulk.tensor.2d.shared::cluster.global.mbarrier::complete_tx::bytes [%0], [%1, {%3, %4}], [%2];"
                 ::"r"(dst), "l"(m), "r"(bar), "r"(c0), "r"(c1) : "memory");
}
__device__ __forceinline__ void ldsm4(uint32_t* r, uint32_t a) {
    asm volatile("ldmatrix.sync.aligned.m8n8.x4.shared.b16 {%0,%1,%2,%3}, [%4];"
                 : "=r"(r[0]), "=r"(r[1]), "=r"(r[2]), "=r"(r[3]) : "r"(a) : "memory");
}
__device__ __forceinline__ void ldsm4t(uint32_t* r, uint32_t a) {
    asm volatile("ldmatrix.sync.aligned.m8n8.x4.trans.shared.b16 {%0,%1,%2,%3}, [%4];"
                 : "=r"(r[0]), "=r"(r[1]), "=r"(r[2]), "=r"(r[3]) : "r"(a) : "memory");
}
__device__ __forceinline__ void mma(float* c, const uint32_t* a, uint32_t b0, uint32_t b1) {
    asm("mma.sync.aligned.m16n8k16.row.col.f32.bf16.bf16.f32 {%0,%1,%2,%3},{%4,%5,%6,%7},{%8,%9},{%0,%1,%2,%3};"
        : "+f"(c[0]), "+f"(c[1]), "+f"(c[2]), "+f"(c[3])
        : "r"(a[0]), "r"(a[1]), "r"(a[2]), "r"(a[3]), "r"(b0), "r"(b1));
}
__device__ __forceinline__ uint4 lds128(uint32_t a) {
    uint4 v;
    asm volatile("ld.shared.v4.u32 {%0,%1,%2,%3}, [%4];" : "=r"(v.x), "=r"(v.y), "=r"(v.z), "=r"(v.w) : "r"(a) : "memory");
    return v;
}
__device__ __forceinline__ float4 lds128f(uint32_t a) {
    float4 v;
    asm volatile("ld.shared.v4.f32 {%0,%1,%2,%3}, [%4];" : "=f"(v.x), "=f"(v.y), "=f"(v.z), "=f"(v.w) : "r"(a) : "memory");
    return v;
}
__device__ __forceinline__ float2 lds64f(uint32_t a) {
    float2 v;
    asm volatile("ld.shared.v2.f32 {%0,%1}, [%2];" : "=f"(v.x), "=f"(v.y) : "r"(a) : "memory");
    return v;
}
__device__ __forceinline__ float lds32f(uint32_t a) {
    float v;
    asm volatile("ld.shared.f32 %0, [%1];" : "=f"(v) : "r"(a) : "memory");
    return v;
}
__device__ __forceinline__ void sts16(uint32_t a, uint32_t v) {
    asm volatile("st.shared.u16 [%0], %1;" ::"r"(a), "h"((unsigned short)v) : "memory");
}
__device__ __forceinline__ void sts32f(uint32_t a, float v) {
    asm volatile("st.shared.f32 [%0], %1;" ::"r"(a), "f"(v) : "memory");
}
__device__ __forceinline__ void cta_sync() { asm volatile("bar.sync 0;" ::: "memory"); }
__device__ __forceinline__ float ex2(float x) {
    float y;
    asm("ex2.approx.ftz.f32 %0, %1;" : "=f"(y) : "f"(x));
    return y;
}
__device__ __forceinline__ float rcp(float x) {
    float y;
    asm("rcp.approx.ftz.f32 %0, %1;" : "=f"(y) : "f"(x));
    return y;
}
__device__ __forceinline__ uint32_t pack_bf16(float lo, float hi) {
    uint32_t r;
    asm("cvt.rn.bf16x2.f32 %0, %1, %2;" : "=r"(r) : "f"(hi), "f"(lo));
    return r;
}
__device__ __forceinline__ float4 ld_relaxed4(const void* p) {
    float4 v;
    asm volatile("ld.relaxed.gpu.global.v4.f32 {%0,%1,%2,%3}, [%4];" : "=f"(v.x), "=f"(v.y), "=f"(v.z), "=f"(v.w) : "l"(p) : "memory");
    return v;
}
__device__ __forceinline__ float2 ld_relaxed2(const void* p) {
    float2 v;
    asm volatile("ld.relaxed.gpu.global.v2.f32 {%0,%1}, [%2];" : "=f"(v.x), "=f"(v.y) : "l"(p) : "memory");
    return v;
}
__device__ __forceinline__ void st_relaxed2(void* p, float x, float y) {
    asm volatile("st.relaxed.gpu.global.v2.f32 [%0], {%1,%2};" ::"l"(p), "f"(x), "f"(y) : "memory");
}
__device__ __forceinline__ void st_relaxed4(void* p, float x, float y, float z, float w) {
    asm volatile("st.relaxed.gpu.global.v4.f32 [%0], {%1,%2,%3,%4};" ::"l"(p), "f"(x), "f"(y), "f"(z), "f"(w) : "memory");
}
__device__ __forceinline__ void red4(void* p, float x, float y, float z, float w) {
    asm volatile("red.relaxed.gpu.global.add.v4.f32 [%0], {%1,%2,%3,%4};" ::"l"(p), "f"(x), "f"(y), "f"(z), "f"(w) : "memory");
}
__device__ __forceinline__ float4 atom4(void* p, float x, float y, float z, float w) {
    float4 v;
    asm volatile("atom.relaxed.gpu.global.add.v4.f32 {%0,%1,%2,%3}, [%4], {%5,%6,%7,%8};"
                 : "=f"(v.x), "=f"(v.y), "=f"(v.z), "=f"(v.w) : "l"(p), "f"(x), "f"(y), "f"(z), "f"(w) : "memory");
    return v;
}
__device__ __forceinline__ constexpr uint32_t eoff(int e) { return (uint32_t)((e & 1) * 128 + (e >> 1) * 512); }

constexpr uint32_t ONES = 0x3F803F80u;

__device__ __forceinline__ void mma_ab(float* c, uint32_t a0, uint32_t a1, uint32_t a2, uint32_t a3, uint32_t b0, uint32_t b1) {
    asm("mma.sync.aligned.m16n8k16.row.col.f32.bf16.bf16.f32 {%0,%1,%2,%3},{%4,%5,%6,%7},{%8,%9},{%0,%1,%2,%3};"
        : "+f"(c[0]), "+f"(c[1]), "+f"(c[2]), "+f"(c[3])
        : "r"(a0), "r"(a1), "r"(a2), "r"(a3), "r"(b0), "r"(b1));
}
__device__ __forceinline__ bool elect_one() {
    uint32_t p;
    asm volatile("{\n.reg .pred p;\nelect.sync _|p, 0xffffffff;\nselp.u32 %0, 1, 0, p;\n}" : "=r"(p));
    return p;
}
__device__ __forceinline__ float rsq(float x) {
    float y;
    asm("rsqrt.approx.ftz.f32 %0, %1;" : "=f"(y) : "f"(x));
    return y;
}
__device__ __forceinline__ uint32_t elapsed(uint32_t c0) {
    uint32_t c;
    asm volatile("mov.u32 %0, %%clock;" : "=r"(c) :: "memory");
    return __shfl_sync(0xffffffffu, c, 0) - c0 ;
}
__device__ __forceinline__ void zero4(float* c) { c[0] = c[1] = c[2] = c[3] = 0.f; }
__device__ __forceinline__ uint32_t pin(uint32_t v, int lane) { return __shfl_sync(0xffffffffu, v, lane); }

__device__ __forceinline__ void ln_partials(const uint4& u0, const uint4& u1, bool godd, float& s, float& q) {
    float c[4], d[4];
    zero4(c); zero4(d);
    mma_ab(c, u0.x, ONES, u0.y, ONES, u0.x, u0.y);
    mma_ab(d, u1.x, ONES, u1.y, ONES, u1.x, u1.y);
    mma_ab(c, u0.z, ONES, u0.w, ONES, u0.z, u0.w);
    mma_ab(d, u1.z, ONES, u1.w, ONES, u1.z, u1.w);
    s = (c[2] + d[2]) + (c[3] + d[3]);
    q = godd ? c[1] + d[1] : c[0] + d[0];
}
__device__ __forceinline__ void ln_finish(float s, float q, float& mean, float& rstd) {
    q += __shfl_xor_sync(0xffffffffu, q, 4);
    s += __shfl_xor_sync(0xffffffffu, s, 1);
    q += __shfl_xor_sync(0xffffffffu, q, 9);
    s += __shfl_xor_sync(0xffffffffu, s, 2);
    q += __shfl_xor_sync(0xffffffffu, q, 18);
    mean = s * (1.f / 512.f);
    q = __shfl_sync(0xffffffffu, q, 0);
    rstd = rsq(fmaxf(fmaf(-mean, mean, q * (1.f / 512.f)), 0.f) + 1e-5f);
}

#define FENCE() __syncwarp()
#define DEP2(x, d1, d2) ((x) | (((d1) | (d2)) & zr))
#define WO_FRAG(j) ldsm4t(Wf[j], (a_wo ^ (((j) & 3) << 5)) + ((j) >> 2) * 2048)

__global__ void __cluster_dims__(2, 1, 1) __launch_bounds__(NTHR, 1)
fused_kernel(const __nv_bfloat16* __restrict__ x_in, __nv_bfloat16* __restrict__ out, unsigned char* const acc_base, MlRow* const g_ml,
             PROF_PARAM const __grid_constant__ Maps mp) {
    extern __shared__ __align__(1024) unsigned char smem[];
    const uint32_t sb = (uint32_t)__cvta_generic_to_shared(smem);
    const int tid = threadIdx.x;
    const int b = blockIdx.x, r = b & 1, pr = (b >> 1) & 1, h = b >> 2;
    unsigned clk0;
    asm volatile("mov.u32 %0, %%clock;" : "=r"(clk0) :: "memory");
    if (tid == 0) {
        mbar_init(sb + OFF_BAR + B_WQ, 1);
        asm volatile("fence.mbarrier_init.release.cluster;" ::: "memory");
        mbar_expect(sb + OFF_BAR + B_WQ, 65536 + 1024);
        asm volatile("cp.async.bulk.shared::cluster.global.mbarrier::complete_tx::bytes [%0], [%1], 1024, [%2];"
                     ::"r"(sb + OFF_PS), "l"(x_in), "r"(sb + OFF_BAR + B_WQ) : "memory");
        tma2d(sb + OFF_WQ, &mp.wq, h * 128 + r * 64, 0, sb + OFF_BAR + B_WQ);
        tma2d(sb + OFF_WQ + 32768, &mp.wq, h * 128 + r * 64, 256, sb + OFF_BAR + B_WQ);
    }
    const uint32_t g0 = gtime();
    clk0 = __shfl_sync(0xffffffffu, clk0, 0);
    const int w = __shfl_sync(0xffffffffu, tid >> 5, 0), lane = tid & 31, g = lane >> 2, t = lane & 3;
    const bool ffn = b < NFFN;
    const uint32_t bars = sb + OFF_BAR + w * BS;
    if (elect_one()) {
        if (w >= 1 && w < 7) asm volatile("prefetch.tensormap [%0];" ::"l"(&mp.wq + w) : "memory");
        mbar_init(bars + B_K, 1); mbar_init(bars + B_V, 1); mbar_init(bars + B_WO, 1); mbar_init(bars + B_F, 1); mbar_init(bars + B_SX, 1);
        asm volatile("fence.mbarrier_init.release.cluster;" ::: "memory");
        mbar_expect(bars + B_SX, 256);
    }
    __syncwarp();
    STAMP(13);
    asm volatile("barrier.cluster.arrive.relaxed.aligned;" ::: "memory");

    unsigned char* const accp = acc_base + pin(w * 4096 + (g >> 1) * 1024 + ((g & 1) * 3 + (t < 3 ? t : 2)) * 16, lane);
    unsigned char* const accw = accp + r * 256;
    const bool own = t < 3;
    uint32_t zdep = 0;
    {
        const int z = tid - 32;
        unsigned char* zp;
        if (z < 16) zp = reinterpret_cast<unsigned char*>(&g_ml[0][b][0]) + (z >> 1) * 16 + 8 + (z & 1) * 4;
        else {
            const int i = b * 48 + (z - 16), e = 1 + (i >> 11), u = (i >> 5) & 63;
            zp = acc_base + (u >> 3) * 4096 + (u & 1) * 256 + ((u >> 1) & 3) * 1024 + (e & 1) * 128 + (e >> 1) * 512 + (i & 31) * 4;
        }
        asm volatile("{\n.reg .pred p;\nsetp.lt.u32 p, %2, 64;\n@p atom.relaxed.gpu.global.exch.b32 %0, [%1], 0;\n}"
                     : "+r"(zdep) : "l"(zp), "r"(z) : "memory");
    }

    const int mi = lane >> 3, li = lane & 7;
    const uint32_t wo_box = sb + (w < 5 ? OFF_K + w * 8192 : OFF_WO5 + (w - 5) * 8192);
    const uint32_t a_gemv = pin(sb + ((mi & 1) * 64 + (mi >> 1) * 8 + li) * 128 + ((w ^ li) << 4), lane);
    const uint32_t a_wo = pin(wo_box + ((mi >> 1) * 8 + li) * 128 + (((mi & 1) ^ li) << 4), lane);
    const uint32_t a_xst = pin(sb + OFF_XS + w * VS + (g >> 1) * 32 + (g & 1) * 2 + t * 12, lane);
    const uint32_t a_pst = pin(sb + OFF_PS + w * VS + (g >> 1) * 32 + (g & 1) * 2 + t * 8, lane);
    const uint32_t a_row = pin(sb + g * VS + t * 32, lane);
    const uint32_t a_qo = pin(sb + (g >> 1) * 32 + w * 4 + (g & 1) * 2, lane);
    const uint32_t a_t32 = pin(sb + t * 32, lane);
    const uint32_t a_sx = pin(sb + tid * 8, lane);
    uint32_t peer_sx, peer_bar;
    asm volatile("mapa.shared::cluster.u32 %0, %1, %2;" : "=r"(peer_sx) : "r"(a_sx), "r"(r ^ 1));
    asm volatile("mapa.shared::cluster.u32 %0, %1, %2;" : "=r"(peer_bar) : "r"(bars + B_SX), "r"(r ^ 1));
    const float2* const mlp = &g_ml[0][0][0] + pin((b ^ 2) * 16 + 2 * g, lane);
    float2* const mlo = &g_ml[0][0][0] + pin(b * 16 + 2 * g, lane);
    const uint32_t a_mg = pin(sb + OFF_M + g * 4, lane), a_mt = pin(sb + OFF_M + t * 8, lane), a_sb = pin(sb, lane), a_bsx = pin(bars + B_SX, lane);
    const uint32_t zr = pin(tid >> 20, lane);

    int todo = 1, vi = 0;
    uint32_t due = (uint32_t)((8 + 2 * w - LEAD) * QNS);
    const int kr = h * 4096 + 3072 + pr * 512;
    auto issue = [&]() {
        const bool el = elect_one();
        if (todo == 1) {
            if (el) { mbar_expect(bars + B_K, 8192); tma2d(sb + OFF_K + w * 8192, &mp.k, r * 64, kr + w * 64, bars + B_K); }
            todo = 0;
        } else if (todo == 2) {
            if (el) {
                const uint32_t bar = sb + OFF_BAR + (vi >> 1) * BS + B_V;
                if (!(vi & 1)) mbar_expect(bar, 16384);
                tma2d(sb + OFF_V + vi * 8192, &mp.v, r * 64, kr + vi * 64, bar);
            }
            vi++; due += 2 * QNS;
            if (vi == 8) todo = 0;
        } else if (todo == 3) {
            if (el) { mbar_expect(bars + B_WO, 8192); tma2d(wo_box, &mp.wo, w * 64, h * 128 + r * 64, bars + B_WO); }
            todo = (ffn && w < 4) ? 4 : 0;
            due = (uint32_t)((FQ - LEAD) * QNS + w * (4 * QNS / 3));
        } else if (todo == 4) {
            if (el) { mbar_expect(bars + B_F, 8192); tma2d(sb + OFF_W13 + w * 8192, (w & 1) ? &mp.w3 : &mp.w1, b * 16, (w >> 1) * 256, bars + B_F); }
            todo = 0;
        } else {
            if (el) {
                mbar_expect(bars + B_F, 4096);
                tma2d(sb + OFF_W2 + (w - 4) * 4096, &mp.w2, (w - 4) * 128, b * 16, bars + B_F);
                tma2d(sb + OFF_W2 + (w - 4) * 4096 + 2048, &mp.w2, (w - 4) * 128 + 64, b * 16, bars + B_F);
            }
            todo = 0;
        }
        __syncwarp();
    };
    uint32_t ka0 = zr, ka1 = zr;
    auto keep = [&]() {
        if (w == 7) asm volatile("mma.sync.aligned.m16n8k8.row.col.f16.f16.f16.f16 {%0,%1},{%2,%2},{%2},{%0,%1};" : "+r"(ka0), "+r"(ka1) : "r"(zr));
    };
    auto gated_wait = [&](uint32_t bar, bool ka = true) {
        int n = SPIN_LIMIT << 4;
        while (!mbar_test(bar) && --n > 0) {
            if (todo && gtime() - g0 >= due) issue();
            if (ka) keep();
            if (!todo && (!ka || w != 7)) { mbar_wait(bar, 0); break; }
        }
    };
    uint32_t Kf[16][4], Vf[16][4], S[16][4], Wf[16][4];
    float cs_q = 0.f, cs_g = 0.f, cs_u = 0.f;
    STAMP(0);
    asm volatile("barrier.cluster.wait.acquire.aligned;" ::: "memory");
    gated_wait(sb + OFF_BAR + B_WQ, false);
    if (todo) issue();
    STAMP(14);
    float xo[3];
#pragma unroll
    for (int i = 0; i < 3; i++) {
        uint32_t xr;
        asm volatile("ld.shared.u16 %0, [%1];" : "=r"(xr) : "r"(sb + OFF_PS + (64 * w + 8 * ((3 * t + i) & 7) + g) * 2) : "memory");
        xo[i] = __uint_as_float(xr << 16);
    }

    uint32_t p01 = 0, p2 = 0;
    auto put_x = [&](float vx, float vy, float vz) {
        p01 = pack_bf16(xo[0] + vx, xo[1] + vy);
        p2 = pack_bf16(xo[2] + vz, 0.f);
        if (own) { sts16(a_xst, p01); sts16(a_xst + 4, p01 >> 16); }
        if (t < 2) sts16(a_xst + 8, p2);
    };
    auto commit_x = [&]() {
        cta_sync();
        p2 |= ka0 & ka1 & 0xffffu;
        xo[0] = __uint_as_float(p01 << 16); xo[1] = __uint_as_float(p01 & 0xffff0000u); xo[2] = __uint_as_float(p2 << 16);
    };
    uint32_t t_red = 0;
    auto exchange_wait = [&](const unsigned char* p, float target, uint32_t delay) {
        int n = SPIN_LIMIT;
        if (delay) while (elapsed(t_red) < delay) keep();
        bool more;
        do {
            const float4 v = ld_relaxed4(p), v2 = ld_relaxed4(p + 256);
            keep();
            --n;
            more = __any_sync(0xffffffffu, v.w + v2.w != target && n > 0);
            put_x(v.x + v2.x, v.y + v2.y, v.z + v2.z);
        } while (more);
        commit_x();
    };

#pragma unroll
    for (int layer = 0; layer < 2; layer++) {
#pragma unroll
        for (int j = 0; j < 16; j++) ldsm4t(S[j], a_gemv + OFF_WQ + ((j >> 2) * 128 + (j & 3) * 16) * 128);
        if (layer == 0) {
            float c0[4], c1[4];
            zero4(c0); zero4(c1);
#pragma unroll
            for (int j = 0; j < 8; j++) { mma(c0, S[2 * j], ONES, ONES); mma(c1, S[2 * j + 1], ONES, ONES); }
            cs_q = ((c0[0] + c0[3]) + (c1[0] + c1[3])) * (1.f / 512.f);
            put_x(0.f, 0.f, 0.f);
            commit_x();
            if (b < 2 && own) red4(accw, 0.5f * xo[0], 0.5f * xo[1], t < 2 ? 0.5f * xo[2] : 0.f, 1.f);
            xo[0] = xo[1] = xo[2] = 0.f;
        } else {
            if (!ffn) { while (gtime() - g0 < P1NS) keep(); exchange_wait(accp + eoff(0), (float)(NCTA + 2), 0); t_red = elapsed(0) + PDN; if (PDN) while ((int)elapsed(t_red) < 0) keep(); }
            exchange_wait(accp + eoff(1), (float)NFFN, PD2);
        }
        STAMP(1 + layer * 14);
        float ls, lq;
        {
            uint4 u0 = lds128(a_row + OFF_XS), u1 = lds128(a_row + OFF_XS + 16);
            float acc[4][4];
#pragma unroll
            for (int a = 0; a < 4; a++) { zero4(acc[a]); mma(acc[a], S[a * 4 + 0], u0.x, u0.y); }
            ln_partials(u0, u1, g & 1, ls, lq);
#pragma unroll
            for (int a = 0; a < 4; a++) mma(acc[a], S[a * 4 + 1], u0.z, u0.w);
#pragma unroll
            for (int a = 0; a < 4; a++) mma(acc[a], S[a * 4 + 2], u1.x, u1.y);
#pragma unroll
            for (int a = 0; a < 4; a++) mma(acc[a], S[a * 4 + 3], u1.z, u1.w);
            float e0 = (t & 2) ? ((t & 1) ? acc[3][0] : acc[2][0]) : ((t & 1) ? acc[1][0] : acc[0][0]);
            float e1 = (t & 2) ? ((t & 1) ? acc[3][3] : acc[2][3]) : ((t & 1) ? acc[1][3] : acc[0][3]);
            float q = fmaf(-ls, cs_q, e0) + e1;
            q += __shfl_xor_sync(0xffffffffu, q, 1);
            q += __shfl_xor_sync(0xffffffffu, q, 2);
            if (t == 0) sts16(a_qo + OFF_QS, pack_bf16(q, 0.f));
        }
        STAMP(2 + layer * 14);
        cta_sync();
        if (layer == 0) {
            if (w == 7) { todo = 2; due = (uint32_t)((24 - LEAD) * QNS); }
            gated_wait(bars + B_K, false);
            while (todo) issue();
#pragma unroll
            for (int j = 0; j < 16; j++)
                ldsm4(Kf[j], sb + OFF_K + w * 8192 + ((j >> 2) * 16 + (mi & 1) * 8 + li) * 128 + ((((j & 3) * 2 + (mi >> 1)) ^ li) << 4));
        }
        float s0, s1, scl;
        {
            uint4 q0 = lds128(a_t32 + OFF_QS), q1 = lds128(a_t32 + OFF_QS + 16);
            float sc[4][4];
#pragma unroll
            for (int j = 0; j < 4; j++) { zero4(sc[j]); mma(sc[j], Kf[j * 4 + 0], q0.x, q0.y); }
#pragma unroll
            for (int j = 0; j < 4; j++) mma(sc[j], Kf[j * 4 + 1], q0.z, q0.w);
#pragma unroll
            for (int j = 0; j < 4; j++) mma(sc[j], Kf[j * 4 + 2], q1.x, q1.y);
#pragma unroll
            for (int j = 0; j < 4; j++) mma(sc[j], Kf[j * 4 + 3], q1.z, q1.w);
            float mean, rstd;
            ln_finish(ls, lq, mean, rstd);
            scl = rstd * (0.08838834764831845f * 1.4426950408889634f);
            s0 = (t & 2) ? ((t & 1) ? sc[3][0] : sc[2][0]) : ((t & 1) ? sc[1][0] : sc[0][0]);
            s1 = (t & 2) ? ((t & 1) ? sc[3][2] : sc[2][2]) : ((t & 1) ? sc[1][2] : sc[0][2]);
            asm volatile("st.async.weak.shared::cluster.mbarrier::complete_tx::bytes.v2.f32 [%0], {%1,%2}, [%3];"
                         ::"r"(peer_sx + (layer ? OFF_SX1 : OFF_SX0)), "f"(s0), "f"(s1), "r"(peer_bar) : "memory");
            FENCE();
            if (layer == 1) {
#pragma unroll
                for (int j = NWO0; j < NWO1; j++) WO_FRAG(j);
            }
        }
        STAMP(3 + layer * 14);
        s0 *= scl; s1 *= scl;
        mbar_wait(a_bsx, layer);
        {
            float2 o2 = lds64f(a_sx + (layer ? OFF_SX1 : OFF_SX0));
            s0 = fmaf(o2.x, scl, s0);
            s1 = fmaf(o2.y, scl, s1);
            int mi_ = __float_as_int(fmaxf(fmaxf(s0, s1), -3.0e38f));
            mi_ ^= (mi_ >> 31) & 0x7fffffff;
            mi_ = __reduce_max_sync(0xffffffffu, mi_);
            mi_ ^= (mi_ >> 31) & 0x7fffffff;
            const float mw = __int_as_float(mi_);
            uint32_t pp = pack_bf16(ex2(s0 - mw), ex2(s1 - mw));
            sts16(a_pst, pp);
            sts16(a_pst + 4, pp >> 16);
            if (lane == 0) sts32f(a_qo + OFF_M, mw);
        }
        STAMP(4 + layer * 14);
        cta_sync();
        float M, tot;
        float2 rem, rem2;
        {
            uint4 u0 = lds128(a_row + OFF_PS), u1 = lds128(a_row + OFF_PS + 16);
            float mg = lds32f(a_mg);
            FENCE();
            float4 m0 = lds128f(a_sb + OFF_M), m1 = lds128f(a_sb + OFF_M + 16);
            float2 mt = lds64f(a_mt);
            if (w == 0) {
                float c[4], d[4];
                zero4(c); zero4(d);
                mma_ab(c, u0.x, u0.y, u0.z, u0.w, ONES, ONES);
                mma_ab(d, u1.x, u1.y, u1.z, u1.w, ONES, ONES);
                const float l0 = (c[1] + c[3]) + (d[1] + d[3]);
                if (t == 0) st_relaxed2(mlo + layer, mg, __uint_as_float(__float_as_uint(l0) | 0x80000000u));
                __syncwarp();
            }
            float acc[4][4];
            if (layer == 0) {
                if (lane == 0) mbar_expect(bars + B_SX, 256);
                asm volatile("{\n.reg .pred p;\nsetp.eq.u32 p, %0, 0x7fd3a5c1;\n@p nanosleep.u32 1;\n}" ::"r"(zdep) : "memory");
                todo = 3; due = (uint32_t)((WOQ - LEAD) * QNS + w * (QNS / 2));
#pragma unroll
                for (int a = 0; a < 4; a++) {
                    if (a == 1) rem = ld_relaxed2(mlp);
                    gated_wait(sb + OFF_BAR + a * BS + B_V, false);
                    if (a == 3) STAMP(27);
#pragma unroll
                    for (int j = 0; j < 4; j++) ldsm4t(Vf[a * 4 + j], a_gemv + OFF_V + (a * 128 + j * 16) * 128);
                    zero4(acc[a]);
                    mma(acc[a], Vf[a * 4 + 0], u0.x, u0.y);
                    mma(acc[a], Vf[a * 4 + 1], u0.z, u0.w);
                    mma(acc[a], Vf[a * 4 + 2], u1.x, u1.y);
                    mma(acc[a], Vf[a * 4 + 3], u1.z, u1.w);
                }
            } else {
#pragma unroll
                for (int a = 0; a < 4; a++) { zero4(acc[a]); mma(acc[a], Vf[a * 4 + 0], u0.x, u0.y); }
                WO_FRAG(NWO1); WO_FRAG(NWO1 + 1); WO_FRAG(NWO1 + 2); WO_FRAG(NWO1 + 3);
                const uint32_t d0 = __float_as_uint(acc[3][1]);
                m0.x = __uint_as_float(DEP2(__float_as_uint(m0.x), d0, d0)); m0.z = __uint_as_float(DEP2(__float_as_uint(m0.z), d0, d0));
                m1.x = __uint_as_float(DEP2(__float_as_uint(m1.x), d0, d0)); m1.z = __uint_as_float(DEP2(__float_as_uint(m1.z), d0, d0));
#pragma unroll
                for (int a = 0; a < 4; a++) mma(acc[a], Vf[a * 4 + 1], u0.z, u0.w);
#pragma unroll
                for (int a = 0; a < 4; a++) mma(acc[a], Vf[a * 4 + 2], u1.x, u1.y);
                uint32_t bz = DEP2(u1.z, Wf[NWO1][0], Wf[NWO1 + 1][0]), bw = DEP2(u1.w, Wf[NWO1 + 2][0], Wf[NWO1 + 3][0]);
#pragma unroll
                for (int a = 0; a < 4; a++) mma(acc[a], Vf[a * 4 + 3], bz, bw);
            }
            M = fmaxf(fmaxf(fmaxf(m0.x, m0.y), fmaxf(m0.z, m0.w)), fmaxf(fmaxf(m1.x, m1.y), fmaxf(m1.z, m1.w)));
            {
                float c[4];
                zero4(c);
                mma_ab(c, u0.x, u0.y, u0.z, u0.w, ONES, ONES);
                mma_ab(c, u1.x, u1.y, u1.z, u1.w, ONES, ONES);
                tot = (c[0] + c[2]) * ex2(mg - M);
            }
            const float f0 = ex2(mt.x - M), f1 = ex2(mt.y - M);
            float e0 = (t & 2) ? ((t & 1) ? acc[3][0] : acc[2][0]) : ((t & 1) ? acc[1][0] : acc[0][0]);
            float e1 = (t & 2) ? ((t & 1) ? acc[3][3] : acc[2][3]) : ((t & 1) ? acc[1][3] : acc[0][3]);
            float o = fmaf(f0, e0, f1 * e1);
            if (layer == 1) { FENCE(); rem = ld_relaxed2(mlp + 1); }
            o += __shfl_xor_sync(0xffffffffu, o, 1);
            o += __shfl_xor_sync(0xffffffffu, o, 2);
            if (t == 0) sts16(a_qo + OFF_OS, pack_bf16(o, 0.f));
        }
        STAMP(5 + layer * 14);
        cta_sync();
        if (layer == 0) {
            if (todo == 3) issue();
            if (w >= 4 && ffn) { todo = 5; due = (uint32_t)((F2Q - LEAD) * QNS); }
            gated_wait(bars + B_WO);
            STAMP(28);
#pragma unroll
            for (int j = 0; j < NWO1 + 4; j++) WO_FRAG(j);
        }
        {
            uint4 o0 = lds128(a_t32 + OFF_OS), o1 = lds128(a_t32 + OFF_OS + 16);
#pragma unroll
            for (int j = NWO1 + 4; j < 16; j++) WO_FRAG(j);
            if (layer == 1) rem2 = ld_relaxed2(mlp + 1); else rem2 = rem;
            FENCE();
            float y[4][4];
#pragma unroll
            for (int j = 0; j < 4; j++) { zero4(y[j]); mma(y[j], Wf[j], o0.x, o0.y); }
#pragma unroll
            for (int j = 0; j < 4; j++) mma(y[j], Wf[4 + j], o0.z, o0.w);
#pragma unroll
            for (int j = 0; j < 4; j++) mma(y[j], Wf[8 + j], o1.x, o1.y);
#pragma unroll
            for (int j = 0; j < 4; j++) mma(y[j], Wf[12 + j], o1.z, o1.w);
            FENCE();
            STAMP(6 + layer * 14);
            if (!__all_sync(0xffffffffu, __float_as_uint(rem.y) != 0u)) {
                rem = rem2;
                int n = 0;
                while (!__all_sync(0xffffffffu, __float_as_uint(rem.y) != 0u) && ++n < SPIN_LIMIT) rem = ld_relaxed2(mlp + layer);
            }
            tot = fmaf(-rem.y, ex2(rem.x - M), tot);
            tot += __shfl_xor_sync(0xffffffffu, tot, 4);
            tot += __shfl_xor_sync(0xffffffffu, tot, 8);
            tot += __shfl_xor_sync(0xffffffffu, tot, 16);
            const float inv = rcp(tot);
            float v0 = (t == 0) ? y[0][0] : (t == 1) ? y[1][2] : y[3][0];
            float v1 = (t == 0) ? y[0][2] : (t == 1) ? y[2][0] : y[3][2];
            float v2 = (t == 0) ? y[1][0] : (t == 1) ? y[2][2] : 0.f;
            if (own) red4(accw + layer * eoff(2), v0 * inv, v1 * inv, v2 * inv, 1.f);
            t_red = elapsed(0);
            if (layer == 1 && w == 0 && t == 0) st_relaxed2(mlo, 0.f, 0.f);
        }
        STAMP(7 + layer * 14);

        if (ffn) {
            const uint32_t a_fst = pin(sb + OFF_FP + (w >> 2) * 256 + ((w & 1) * 8 + g) * 16 + ((w >> 1) & 1) * 8, lane);
            const bool fst = t == (w >> 1);
            const uint32_t a_frd = pin(sb + OFF_FP + (lane & 15) * 16, lane);
            const uint32_t a_w2 = sb + OFF_W2 + w * 2048 + ((mi >> 1) * 8 + li) * 128 + (((mi & 1) ^ li) << 4);
            if (layer == 0) {
                while (todo) { if (gtime() - g0 >= due) issue(); keep(); }
            }
            const uint32_t a_w13 = sb + OFF_W13 + (w >> 2) * 16384 + (mi & 1) * 8192 + (((w >> 1) & 1) * 128 + (mi >> 1) * 8 + li) * 32 + (((w & 1) ^ (li >> 2)) << 4);
            auto stage_w13 = [&]() {
#pragma unroll
                for (int j = 0; j < 8; j++) ldsm4t(S[j], a_w13 + j * 16 * 32);
                if (layer == 0) {
                    float c0[4], c1[4];
                    zero4(c0); zero4(c1);
#pragma unroll
                    for (int j = 0; j < 4; j++) { mma(c0, S[2 * j], ONES, ONES); mma(c1, S[2 * j + 1], ONES, ONES); }
                    if (t == 0) asm volatile("st.shared.v2.f32 [%0], {%1,%2};" ::"r"(a_fst + (OFF_FC - OFF_FP)), "f"(c0[0] + c1[0]), "f"(c0[2] + c1[2]) : "memory");
                }
            };
            if (layer == 0) {
                const uint32_t bw1 = sb + OFF_BAR + (w >> 2) * 2 * BS + B_F;
                bool staged = false, more;
                int n = SPIN_LIMIT;
                while (gtime() - g0 < P1NS) {
                    keep();
                    if (!staged && mbar_test(bw1) && mbar_test(bw1 + BS)) { stage_w13(); staged = true; }
                }
                do {
                    const float4 v = ld_relaxed4(accp), v2 = ld_relaxed4(accp + 256);
                    keep();
                    if (!staged && mbar_test(bw1) && mbar_test(bw1 + BS)) { stage_w13(); staged = true; }
                    --n;
                    more = __any_sync(0xffffffffu, v.w + v2.w != (float)(NCTA + 2) && n > 0);
                    put_x(v.x + v2.x, v.y + v2.y, v.z + v2.z);
                } while (more);
                STAMP(8);
                if (!staged) { gated_wait(bw1); gated_wait(bw1 + BS); STAMP(29); stage_w13(); }
                commit_x();
            } else {
                stage_w13();
#pragma unroll
                for (int j = 0; j < 4; j++) ldsm4t(S[8 + j], a_w2 ^ (j << 5));
                STAMP(8 + layer * 14);
                exchange_wait(accp + eoff(2), (float)NCTA, PD3);
            }
            STAMP(9 + layer * 14);
            {
                uint4 u0 = lds128(a_row + OFF_XS), u1 = lds128(a_row + OFF_XS + 16);
                if (layer == 0) {
                    float4 p0 = lds128f(a_frd + (OFF_FC - OFF_FP)), p1 = lds128f(a_frd + (OFF_FC - OFF_FP) + 256);
                    cs_g = (p0.x + p0.z) + (p1.x + p1.z);
                    cs_u = (p0.y + p0.w) + (p1.y + p1.w);
                }
                {
                    const uint32_t z0 = own ? p01 : 0u, z1 = t < 2 ? p2 : 0u;
                    float c[4];
                    zero4(c);
                    mma_ab(c, z0, ONES, z1, ONES, z0, z1);
                    float s_ = c[2] + c[3], q_ = (g & 1) ? c[1] : c[0];
                    q_ += __shfl_xor_sync(0xffffffffu, q_, 4);
                    s_ += __shfl_xor_sync(0xffffffffu, s_, 1);
                    q_ += __shfl_xor_sync(0xffffffffu, q_, 9);
                    s_ += __shfl_xor_sync(0xffffffffu, s_, 2);
                    q_ += __shfl_xor_sync(0xffffffffu, q_, 18);
                    if (lane == 0) { sts32f(a_qo + OFF_SQ, s_); sts32f(a_qo + OFF_SQ + 32, q_); }
                }
                float acc[4][4];
                zero4(acc[0]); zero4(acc[1]); zero4(acc[2]); zero4(acc[3]);
                mma(acc[0], S[0], u0.x, u0.y); mma(acc[1], S[4], u0.x, u0.y); mma(acc[2], S[2], u1.x, u1.y); mma(acc[3], S[6], u1.x, u1.y);
                mma(acc[0], S[1], u0.z, u0.w); mma(acc[1], S[5], u0.z, u0.w); mma(acc[2], S[3], u1.z, u1.w); mma(acc[3], S[7], u1.z, u1.w);
                if (fst) asm volatile("st.shared.v2.f32 [%0], {%1,%2};" ::"r"(a_fst), "f"((acc[0][0] + acc[2][0]) + (acc[1][1] + acc[3][1])),
                                      "f"((acc[0][2] + acc[2][2]) + (acc[1][3] + acc[3][3])) : "memory");
            }
            STAMP(10 + layer * 14);
            cta_sync();
            {
                const float4 s0 = lds128f(a_sb + OFF_SQ), s1 = lds128f(a_sb + OFF_SQ + 16), q0 = lds128f(a_sb + OFF_SQ + 32), q1 = lds128f(a_sb + OFF_SQ + 48);
                float4 p0 = lds128f(a_frd), p1 = lds128f(a_frd + 256);
                const float mean2 = (((s0.x + s0.y) + (s0.z + s0.w)) + ((s1.x + s1.y) + (s1.z + s1.w))) * (1.f / 512.f);
                const float ssq = ((q0.x + q0.y) + (q0.z + q0.w)) + ((q1.x + q1.y) + (q1.z + q1.w));
                const float rstd2 = rsq(fmaxf(fmaf(-mean2, mean2, fmaf(ssq, 1.f / 512.f, 1e-5f)), 1e-5f));
                if (layer == 0) {
                    mbar_wait(sb + OFF_BAR + (4 + (w >> 1)) * BS + B_F, 0);
#pragma unroll
                    for (int j = 0; j < 4; j++) ldsm4t(S[8 + j], a_w2 ^ (j << 5));
                }
                float gate = rstd2 * (fmaf(-mean2, cs_g, p0.x + p0.z) + (p1.x + p1.z));
                float up = rstd2 * (fmaf(-mean2, cs_u, p0.y + p0.w) + (p1.y + p1.w));
                float hv = gate * up * rcp(1.f + ex2(-1.4426950408889634f * gate));
                float h0 = __shfl_sync(0xffffffffu, hv, 2 * t), h1 = __shfl_sync(0xffffffffu, hv, 2 * t + 1);
                float h2 = __shfl_sync(0xffffffffu, hv, 2 * t + 8), h3 = __shfl_sync(0xffffffffu, hv, 2 * t + 9);
                const uint32_t b0 = pack_bf16(h0, h1), b1 = pack_bf16(h2, h3);
                float y[4][4];
#pragma unroll
                for (int j = 0; j < 4; j++) {
                    zero4(y[j]);
                    mma(y[j], S[8 + j], b0, b1);
                }
                float v0 = (t == 0) ? y[0][0] : (t == 1) ? y[1][2] : y[3][0];
                float v1 = (t == 0) ? y[0][2] : (t == 1) ? y[2][0] : y[3][2];
                float v2 = (t == 0) ? y[1][0] : (t == 1) ? y[2][2] : 0.f;
                STAMP(11 + layer * 14);
                if (layer == 0) {
                    if (own) red4(accw + eoff(1), v0, v1, v2, 1.f);
                    t_red = elapsed(0);
                } else if (own) {
                    float4 old = atom4(accp + eoff(3) + (g & 1) * 208, v0, v1, v2, 1.f);
                    if (b < 2) st_relaxed4(accw + eoff(0), 0.f, 0.f, 0.f, 0.f);
                    if (old.w == (float)(NFFN - 1)) {
                        const int c = 64 * w + 24 * t + g;
                        out[c] = __float2bfloat16(xo[0] + (old.x + v0));
                        out[c + 8] = __float2bfloat16(xo[1] + (old.y + v1));
                        if (t < 2) out[c + 16] = __float2bfloat16(xo[2] + (old.z + v2));
                    }
                }
            }
            STAMP(12 + layer * 14);
        }
    }
}

typedef CUresult (*EncodeFn)(CUtensorMap*, CUtensorMapDataType, cuuint32_t, void*, const cuuint64_t*, const cuuint64_t*,
                             const cuuint32_t*, const cuuint32_t*, CUtensorMapInterleave, CUtensorMapSwizzle,
                             CUtensorMapL2promotion, CUtensorMapFloatOOBfill);

void make_map(EncodeFn enc, CUtensorMap* m, const void* p, uint64_t cols, uint64_t rows, uint32_t bc, uint32_t br) {
    cuuint64_t gd[2] = {cols, rows};
    cuuint64_t gs[1] = {cols * 2};
    cuuint32_t bd[2] = {bc, br};
    cuuint32_t es[2] = {1, 1};
    enc(m, CU_TENSOR_MAP_DATA_TYPE_BFLOAT16, 2, const_cast<void*>(p), gd, gs, bd, es, CU_TENSOR_MAP_INTERLEAVE_NONE,
        bc == 64 ? CU_TENSOR_MAP_SWIZZLE_128B : CU_TENSOR_MAP_SWIZZLE_32B, CU_TENSOR_MAP_L2_PROMOTION_NONE,
        CU_TENSOR_MAP_FLOAT_OOB_FILL_NONE);
}

}

extern "C" void kernel_launch(void* const* d_in, const int* in_sizes, int n_in, void* d_out, int out_size) {
    (void)in_sizes; (void)n_in; (void)out_size;
    static EncodeFn enc = nullptr;
    static unsigned char* acc = nullptr;
    static MlRow* ml = nullptr;
    if (!enc) {
        void* p = nullptr;
        cudaGetSymbolAddress(&p, g_acc_raw);
        acc = reinterpret_cast<unsigned char*>((reinterpret_cast<uintptr_t>(p) + 32767) & ~(uintptr_t)32767);
        cudaGetSymbolAddress(&p, g_ml_buf);
        ml = reinterpret_cast<MlRow*>(p);
        cudaDriverEntryPointQueryResult qr;
        void* fn = nullptr;
        cudaGetDriverEntryPoint("cuTensorMapEncodeTiled", &fn, cudaEnableDefault, &qr);
        enc = (EncodeFn)fn;
        cudaFuncSetAttribute(fused_kernel, cudaFuncAttributeMaxDynamicSharedMemorySize, (int)SMEM_BYTES);
    }
    Maps mp;
    make_map(enc, &mp.wq, d_in[3], 4096, 512, 64, 256);
    make_map(enc, &mp.k, d_in[1], 128, 32 * 4096, 64, 64);
    make_map(enc, &mp.v, d_in[2], 128, 32 * 4096, 64, 64);
    make_map(enc, &mp.wo, d_in[4], 512, 4096, 64, 64);
    make_map(enc, &mp.w1, d_in[6], 1376, 512, 16, 256);
    make_map(enc, &mp.w3, d_in[7], 1376, 512, 16, 256);
    make_map(enc, &mp.w2, d_in[8], 512, 1376, 64, 16);
    fused_kernel<<<NCTA, NTHR, SMEM_BYTES>>>((const __nv_bfloat16*)d_in[0], (__nv_bfloat16*)d_out, acc, ml, mp);
}
```

```cpp
#include <cuda_runtime.h>
#include <cuda_bf16.h>
#include <cuda.h>
#include <stdint.h>

namespace {

constexpr int NCTA = 128;
constexpr int NTHR = 256;
constexpr int NFFN = 86;
constexpr int NWO0 = 3;
constexpr int NWO1 = 8;
constexpr uint32_t PD2 = 500u;
constexpr uint32_t PD3 = 480u;
constexpr uint32_t PDN = 700u;
constexpr int QNS = 155;
constexpr int LEAD = 5;
constexpr int FQ = 46;
constexpr int F2Q = 62;
constexpr int WOQ = 40;
constexpr uint32_t P1NS = 8800u;
constexpr int SPIN_LIMIT = 1 << 20;

constexpr uint32_t OFF_WQ = 0;
constexpr uint32_t OFF_K = 65536;
constexpr uint32_t OFF_W13 = OFF_K + 5 * 8192;
constexpr uint32_t OFF_SX0 = OFF_K + 65536;
constexpr uint32_t OFF_WO5 = OFF_SX0 + 8192;
constexpr uint32_t OFF_V = OFF_WO5 + 24576;
constexpr uint32_t OFF_W2 = OFF_V;
constexpr uint32_t OFF_SX1 = OFF_V + 16384;
constexpr uint32_t OFF_FP = OFF_SX1 + 2048;
constexpr uint32_t OFF_FC = OFF_FP + 512;
constexpr uint32_t VS = 144;
constexpr uint32_t OFF_XS = OFF_V + 65536;
constexpr uint32_t OFF_PS = OFF_XS + 1152;
constexpr uint32_t OFF_QS = OFF_PS + 1152;
constexpr uint32_t OFF_OS = OFF_QS + 128;
constexpr uint32_t OFF_M = OFF_OS + 128;
constexpr uint32_t OFF_SQ = OFF_M + 32;
constexpr uint32_t OFF_BAR = OFF_SQ + 64;
constexpr uint32_t BS = 48;
constexpr uint32_t B_WQ = 0, B_K = 8, B_V = 16, B_WO = 24, B_F = 32, B_SX = 40;
constexpr uint32_t SMEM_BYTES = OFF_BAR + 8 * BS;
static_assert(SMEM_BYTES <= 232448, "smem");

struct Maps { CUtensorMap wq, k, v, wo, w1, w3, w2; };

typedef float2 MlRow[NCTA][16];
__device__ __align__(128) unsigned char g_acc_raw[65536];
__device__ __align__(128) float2 g_ml_buf[1][NCTA][16];

__device__ __forceinline__ void mbar_init(uint32_t a, int c) {
    asm volatile("mbarrier.init.shared::cta.b64 [%0], %1;" ::"r"(a), "r"(c) : "memory");
}
__device__ __forceinline__ void mbar_expect(uint32_t a, uint32_t bytes) {
    asm volatile("mbarrier.arrive.expect_tx.shared::cta.b64 _, [%0], %1;" ::"r"(a), "r"(bytes) : "memory");
}
__device__ __forceinline__ void mbar_wait(uint32_t a, uint32_t parity) {
    uint32_t ok;
    int n = 0;
    do {
        asm volatile("{\n.reg .pred p;\nmbarrier.try_wait.parity.shared::cta.b64 p, [%1], %2;\nselp.u32 %0, 1, 0, p;\n}"
                     : "=r"(ok) : "r"(a), "r"(parity) : "memory");
    } while (!ok && ++n < SPIN_LIMIT);
}
__device__ __forceinline__ bool mbar_test(uint32_t a) {
    uint32_t ok;
    asm volatile("{\n.reg .pred p;\nmbarrier.test_wait.parity.shared::cta.b64 p, [%1], 0;\nselp.u32 %0, 1, 0, p;\n}" : "=r"(ok) : "r"(a) : "memory");
    return ok;
}
__device__ __forceinline__ uint32_t gtime() {
    uint32_t c;
    asm volatile("mov.u32 %0, %%globaltimer_lo;" : "=r"(c) :: "memory");
    return __shfl_sync(0xffffffffu, c, 0);
}
__device__ __forceinline__ void tma2d(uint32_t dst, const CUtensorMap* m, int c0, int c1, uint32_t bar) {
    asm volatile("cp.async.bulk.tensor.2d.shared::cluster.global.mbarrier::complete_tx::bytes [%0], [%1, {%3, %4}], [%2];"
                 ::"r"(dst), "l"(m), "r"(bar), "r"(c0), "r"(c1) : "memory");
}
__device__ __forceinline__ void ldsm4(uint32_t* r, uint32_t a) {
    asm volatile("ldmatrix.sync.aligned.m8n8.x4.shared.b16 {%0,%1,%2,%3}, [%4];"
                 : "=r"(r[0]), "=r"(r[1]), "=r"(r[2]), "=r"(r[3]) : "r"(a) : "memory");
}
__device__ __forceinline__ void ldsm4t(uint32_t* r, uint32_t a) {
    asm volatile("ldmatrix.sync.aligned.m8n8.x4.trans.shared.b16 {%0,%1,%2,%3}, [%4];"
                 : "=r"(r[0]), "=r"(r[1]), "=r"(r[2]), "=r"(r[3]) : "r"(a) : "memory");
}
__device__ __forceinline__ void mma(float* c, const uint32_t* a, uint32_t b0, uint32_t b1) {
    asm("mma.sync.aligned.m16n8k16.row.col.f32.bf16.bf16.f32 {%0,%1,%2,%3},{%4,%5,%6,%7},{%8,%9},{%0,%1,%2,%3};"
        : "+f"(c[0]), "+f"(c[1]), "+f"(c[2]), "+f"(c[3])
        : "r"(a[0]), "r"(a[1]), "r"(a[2]), "r"(a[3]), "r"(b0), "r"(b1));
}
__device__ __forceinline__ uint4 lds128(uint32_t a) {
    uint4 v;
    asm volatile("ld.shared.v4.u32 {%0,%1,%2,%3}, [%4];" : "=r"(v.x), "=r"(v.y), "=r"(v.z), "=r"(v.w) : "r"(a) : "memory");
    return v;
}
__device__ __forceinline__ float4 lds128f(uint32_t a) {
    float4 v;
    asm volatile("ld.shared.v4.f32 {%0,%1,%2,%3}, [%4];" : "=f"(v.x), "=f"(v.y), "=f"(v.z), "=f"(v.w) : "r"(a) : "memory");
    return v;
}
__device__ __forceinline__ float2 lds64f(uint32_t a) {
    float2 v;
    asm volatile("ld.shared.v2.f32 {%0,%1}, [%2];" : "=f"(v.x), "=f"(v.y) : "r"(a) : "memory");
    return v;
}
__device__ __forceinline__ float lds32f(uint32_t a) {
    float v;
    asm volatile("ld.shared.f32 %0, [%1];" : "=f"(v) : "r"(a) : "memory");
    return v;
}
__device__ __forceinline__ void sts16(uint32_t a, uint32_t v) {
    asm volatile("st.shared.u16 [%0], %1;" ::"r"(a), "h"((unsigned short)v) : "memory");
}
__device__ __forceinline__ void sts32f(uint32_t a, float v) {
    asm volatile("st.shared.f32 [%0], %1;" ::"r"(a), "f"(v) : "memory");
}
__device__ __forceinline__ void cta_sync() { asm volatile("bar.sync 0;" ::: "memory"); }
__device__ __forceinline__ float ex2(float x) {
    float y;
    asm("ex2.approx.ftz.f32 %0, %1;" : "=f"(y) : "f"(x));
    return y;
}
__device__ __forceinline__ float rcp(float x) {
    float y;
    asm("rcp.approx.ftz.f32 %0, %1;" : "=f"(y) : "f"(x));
    return y;
}
__device__ __forceinline__ uint32_t pack_bf16(float lo, float hi) {
    uint32_t r;
    asm("cvt.rn.bf16x2.f32 %0, %1, %2;" : "=r"(r) : "f"(hi), "f"(lo));
    return r;
}
__device__ __forceinline__ float4 ld_relaxed4(const void* p) {
    float4 v;
    asm volatile("ld.relaxed.gpu.global.v4.f32 {%0,%1,%2,%3}, [%4];" : "=f"(v.x), "=f"(v.y), "=f"(v.z), "=f"(v.w) : "l"(p) : "memory");
    return v;
}
__device__ __forceinline__ float2 ld_relaxed2(const void* p) {
    float2 v;
    asm volatile("ld.relaxed.gpu.global.v2.f32 {%0,%1}, [%2];" : "=f"(v.x), "=f"(v.y) : "l"(p) : "memory");
    return v;
}
__device__ __forceinline__ void st_relaxed2(void* p, float x, float y) {
    asm volatile("st.relaxed.gpu.global.v2.f32 [%0], {%1,%2};" ::"l"(p), "f"(x), "f"(y) : "memory");
}
__device__ __forceinline__ void st_relaxed4(void* p, float x, float y, float z, float w) {
    asm volatile("st.relaxed.gpu.global.v4.f32 [%0], {%1,%2,%3,%4};" ::"l"(p), "f"(x), "f"(y), "f"(z), "f"(w) : "memory");
}
__device__ __forceinline__ void red4(void* p, float x, float y, float z, float w) {
    asm volatile("red.relaxed.gpu.global.add.v4.f32 [%0], {%1,%2,%3,%4};" ::"l"(p), "f"(x), "f"(y), "f"(z), "f"(w) : "memory");
}
__device__ __forceinline__ float4 atom4(void* p, float x, float y, float z, float w) {
    float4 v;
    asm volatile("atom.relaxed.gpu.global.add.v4.f32 {%0,%1,%2,%3}, [%4], {%5,%6,%7,%8};"
                 : "=f"(v.x), "=f"(v.y), "=f"(v.z), "=f"(v.w) : "l"(p), "f"(x), "f"(y), "f"(z), "f"(w) : "memory");
    return v;
}
__device__ __forceinline__ constexpr uint32_t eoff(int e) { return (uint32_t)((e & 1) * 128 + (e >> 1) * 512); }

constexpr uint32_t ONES = 0x3F803F80u;

__device__ __forceinline__ void mma_ab(float* c, uint32_t a0, uint32_t a1, uint32_t a2, uint32_t a3, uint32_t b0, uint32_t b1) {
    asm("mma.sync.aligned.m16n8k16.row.col.f32.bf16.bf16.f32 {%0,%1,%2,%3},{%4,%5,%6,%7},{%8,%9},{%0,%1,%2,%3};"
        : "+f"(c[0]), "+f"(c[1]), "+f"(c[2]), "+f"(c[3])
        : "r"(a0), "r"(a1), "r"(a2), "r"(a3), "r"(b0), "r"(b1));
}
__device__ __forceinline__ bool elect_one() {
    uint32_t p;
    asm volatile("{\n.reg .pred p;\nelect.sync _|p, 0xffffffff;\nselp.u32 %0, 1, 0, p;\n}" : "=r"(p));
    return p;
}
__device__ __forceinline__ float rsq(float x) {
    float y;
    asm("rsqrt.approx.ftz.f32 %0, %1;" : "=f"(y) : "f"(x));
    return y;
}
__device__ __forceinline__ uint32_t elapsed(uint32_t c0) {
    uint32_t c;
    asm volatile("mov.u32 %0, %%clock;" : "=r"(c) :: "memory");
    return __shfl_sync(0xffffffffu, c, 0) - c0 ;
}
__device__ __forceinline__ void zero4(float* c) { c[0] = c[1] = c[2] = c[3] = 0.f; }
__device__ __forceinline__ uint32_t pin(uint32_t v, int lane) { return __shfl_sync(0xffffffffu, v, lane); }

__device__ __forceinline__ void ln_partials(const uint4& u0, const uint4& u1, bool godd, float& s, float& q) {
    float c[4], d[4];
    zero4(c); zero4(d);
    mma_ab(c, u0.x, ONES, u0.y, ONES, u0.x, u0.y);
    mma_ab(d, u1.x, ONES, u1.y, ONES, u1.x, u1.y);
    mma_ab(c, u0.z, ONES, u0.w, ONES, u0.z, u0.w);
    mma_ab(d, u1.z, ONES, u1.w, ONES, u1.z, u1.w);
    s = (c[2] + d[2]) + (c[3] + d[3]);
    q = godd ? c[1] + d[1] : c[0] + d[0];
}
__device__ __forceinline__ void ln_finish(float s, float q, float& mean, float& rstd) {
    q += __shfl_xor_sync(0xffffffffu, q, 4);
    s += __shfl_xor_sync(0xffffffffu, s, 1);
    q += __shfl_xor_sync(0xffffffffu, q, 9);
    s += __shfl_xor_sync(0xffffffffu, s, 2);
    q += __shfl_xor_sync(0xffffffffu, q, 18);
    mean = s * (1.f / 512.f);
    q = __shfl_sync(0xffffffffu, q, 0);
    rstd = rsq(fmaxf(fmaf(-mean, mean, q * (1.f / 512.f)), 0.f) + 1e-5f);
}

#define FENCE() __syncwarp()
#define DEP2(x, d1, d2) ((x) | (((d1) | (d2)) & zr))
#define WO_FRAG(j) ldsm4t(Wf[j], (a_wo ^ (((j) & 3) << 5)) + ((j) >> 2) * 2048)

__global__ void __cluster_dims__(2, 1, 1) __launch_bounds__(NTHR, 1)
fused_kernel(const __nv_bfloat16* __restrict__ x_in, __nv_bfloat16* __restrict__ out, unsigned char* const acc_base, MlRow* const g_ml,
             const __grid_constant__ Maps mp) {
    extern __shared__ __align__(1024) unsigned char smem[];
    const uint32_t sb = (uint32_t)__cvta_generic_to_shared(smem);
    const int tid = threadIdx.x;
    const int b = blockIdx.x, r = b & 1, pr = (b >> 1) & 1, h = b >> 2;
    if (tid == 0) {
        mbar_init(sb + OFF_BAR + B_WQ, 1);
        asm volatile("fence.mbarrier_init.release.cluster;" ::: "memory");
        mbar_expect(sb + OFF_BAR + B_WQ, 65536 + 1024);
        asm volatile("cp.async.bulk.shared::cluster.global.mbarrier::complete_tx::bytes [%0], [%1], 1024, [%2];"
                     ::"r"(sb + OFF_PS), "l"(x_in), "r"(sb + OFF_BAR + B_WQ) : "memory");
        tma2d(sb + OFF_WQ, &mp.wq, h * 128 + r * 64, 0, sb + OFF_BAR + B_WQ);
        tma2d(sb + OFF_WQ + 32768, &mp.wq, h * 128 + r * 64, 256, sb + OFF_BAR + B_WQ);
    }
    const uint32_t g0 = gtime();
    const int w = __shfl_sync(0xffffffffu, tid >> 5, 0), lane = tid & 31, g = lane >> 2, t = lane & 3;
    const bool ffn = b < NFFN;
    const uint32_t bars = sb + OFF_BAR + w * BS;
    if (elect_one()) {
        if (w >= 1 && w < 7) asm volatile("prefetch.tensormap [%0];" ::"l"(&mp.wq + w) : "memory");
        mbar_init(bars + B_K, 1); mbar_init(bars + B_V, 1); mbar_init(bars + B_WO, 1); mbar_init(bars + B_F, 1); mbar_init(bars + B_SX, 1);
        asm volatile("fence.mbarrier_init.release.cluster;" ::: "memory");
        mbar_expect(bars + B_SX, 256);
    }
    __syncwarp();
    asm volatile("barrier.cluster.arrive.relaxed.aligned;" ::: "memory");

    unsigned char* const accp = acc_base + pin(w * 4096 + (g >> 1) * 1024 + ((g & 1) * 3 + (t < 3 ? t : 2)) * 16, lane);
    unsigned char* const accw = accp + r * 256;
    const bool own = t < 3;
    uint32_t zdep = 0;
    {
        const int z = tid - 32;
        unsigned char* zp;
        if (z < 16) zp = reinterpret_cast<unsigned char*>(&g_ml[0][b][0]) + (z >> 1) * 16 + 8 + (z & 1) * 4;
        else {
            const int i = b * 48 + (z - 16), e = 1 + (i >> 11), u = (i >> 5) & 63;
            zp = acc_base + (u >> 3) * 4096 + (u & 1) * 256 + ((u >> 1) & 3) * 1024 + (e & 1) * 128 + (e >> 1) * 512 + (i & 31) * 4;
        }
        asm volatile("{\n.reg .pred p;\nsetp.lt.u32 p, %2, 64;\n@p atom.relaxed.gpu.global.exch.b32 %0, [%1], 0;\n}"
                     : "+r"(zdep) : "l"(zp), "r"(z) : "memory");
    }

    const int mi = lane >> 3, li = lane & 7;
    const uint32_t wo_box = sb + (w < 5 ? OFF_K + w * 8192 : OFF_WO5 + (w - 5) * 8192);
    const uint32_t a_gemv = pin(sb + ((mi & 1) * 64 + (mi >> 1) * 8 + li) * 128 + ((w ^ li) << 4), lane);
    const uint32_t a_wo = pin(wo_box + ((mi >> 1) * 8 + li) * 128 + (((mi & 1) ^ li) << 4), lane);
    const uint32_t a_xst = pin(sb + OFF_XS + w * VS + (g >> 1) * 32 + (g & 1) * 2 + t * 12, lane);
    const uint32_t a_pst = pin(sb + OFF_PS + w * VS + (g >> 1) * 32 + (g & 1) * 2 + t * 8, lane);
    const uint32_t a_row = pin(sb + g * VS + t * 32, lane);
    const uint32_t a_qo = pin(sb + (g >> 1) * 32 + w * 4 + (g & 1) * 2, lane);
    const uint32_t a_t32 = pin(sb + t * 32, lane);
    const uint32_t a_sx = pin(sb + tid * 8, lane);
    uint32_t peer_sx, peer_bar;
    asm volatile("mapa.shared::cluster.u32 %0, %1, %2;" : "=r"(peer_sx) : "r"(a_sx), "r"(r ^ 1));
    asm volatile("mapa.shared::cluster.u32 %0, %1, %2;" : "=r"(peer_bar) : "r"(bars + B_SX), "r"(r ^ 1));
    const float2* const mlp = &g_ml[0][0][0] + pin((b ^ 2) * 16 + 2 * g, lane);
    float2* const mlo = &g_ml[0][0][0] + pin(b * 16 + 2 * g, lane);
    const uint32_t a_mg = pin(sb + OFF_M + g * 4, lane), a_mt = pin(sb + OFF_M + t * 8, lane), a_sb = pin(sb, lane), a_bsx = pin(bars + B_SX, lane);
    const uint32_t zr = pin(tid >> 20, lane);


    int todo = 1, vi = 0;
    uint32_t due = (uint32_t)((8 + 2 * w - LEAD) * QNS);
    const int kr = h * 4096 + 3072 + pr * 512;
    auto issue = [&](int mask) {
        const bool el = elect_one();
        if ((mask & 2) && todo == 1) {
            if (el) { mbar_expect(bars + B_K, 8192); tma2d(sb + OFF_K + w * 8192, &mp.k, r * 64, kr + w * 64, bars + B_K); }
            todo = 0;
        } else if ((mask & 4) && todo == 2) {
            if (el) {
                const uint32_t bar = sb + OFF_BAR + (vi >> 1) * BS + B_V;
                if (!(vi & 1)) mbar_expect(bar, 16384);
                tma2d(sb + OFF_V + vi * 8192, &mp.v, r * 64, kr + vi * 64, bar);
            }
            vi++; due += 2 * QNS;
            if (vi == 8) todo = 0;
        } else if ((mask & 8) && todo == 3) {
            if (el) { mbar_expect(bars + B_WO, 8192); tma2d(wo_box, &mp.wo, w * 64, h * 128 + r * 64, bars + B_WO); }
            todo = (ffn && w < 4) ? 4 : 0;
            due = (uint32_t)((FQ - LEAD) * QNS + w * (4 * QNS / 3));
        } else if ((mask & 16) && todo == 4) {
            if (el) { mbar_expect(bars + B_F, 8192); tma2d(sb + OFF_W13 + w * 8192, (w & 1) ? &mp.w3 : &mp.w1, b * 16, (w >> 1) * 256, bars + B_F); }
            todo = 0;
        } else if (mask & 32) {
            if (el) {
                mbar_expect(bars + B_F, 4096);
                tma2d(sb + OFF_W2 + (w - 4) * 4096, &mp.w2, (w - 4) * 128, b * 16, bars + B_F);
                tma2d(sb + OFF_W2 + (w - 4) * 4096 + 2048, &mp.w2, (w - 4) * 128 + 64, b * 16, bars + B_F);
            }
            todo = 0;
        }
        __syncwarp();
    };
    uint32_t ka0 = zr, ka1 = zr;
    auto keep = [&]() {
        if (w == 7) asm volatile("mma.sync.aligned.m16n8k8.row.col.f16.f16.f16.f16 {%0,%1},{%2,%2},{%2},{%0,%1};" : "+r"(ka0), "+r"(ka1) : "r"(zr));
    };
    auto gated_wait = [&](uint32_t bar, int mask, bool ka) {
        int n = SPIN_LIMIT << 4;
        while (!mbar_test(bar) && --n > 0) {
            if (mask && todo && gtime() - g0 >= due) issue(mask);
            if (ka) keep();
            if (!todo && (!ka || w != 7)) { mbar_wait(bar, 0); break; }
        }
    };
    uint32_t Kf[16][4], Vf[16][4], S[16][4], Wf[16][4];
    float cs_q = 0.f, cs_g = 0.f, cs_u = 0.f;
    asm volatile("barrier.cluster.wait.acquire.aligned;" ::: "memory");
    gated_wait(sb + OFF_BAR + B_WQ, 2, false);
    if (todo) issue(2);
    float xo[3];
#pragma unroll
    for (int i = 0; i < 3; i++) {
        uint32_t xr;
        asm volatile("ld.shared.u16 %0, [%1];" : "=r"(xr) : "r"(sb + OFF_PS + (64 * w + 8 * ((3 * t + i) & 7) + g) * 2) : "memory");
        xo[i] = __uint_as_float(xr << 16);
    }

    uint32_t p01 = 0, p2 = 0;
    auto put_x = [&](float vx, float vy, float vz) {
        p01 = pack_bf16(xo[0] + vx, xo[1] + vy);
        p2 = pack_bf16(xo[2] + vz, 0.f);
        if (own) { sts16(a_xst, p01); sts16(a_xst + 4, p01 >> 16); }
        if (t < 2) sts16(a_xst + 8, p2);
    };
    auto commit_x = [&]() {
        cta_sync();
        p2 |= ka0 & ka1 & 0xffffu;
        xo[0] = __uint_as_float(p01 << 16); xo[1] = __uint_as_float(p01 & 0xffff0000u); xo[2] = __uint_as_float(p2 << 16);
    };
    uint32_t t_red = 0;
    auto exchange_wait = [&](const unsigned char* p, float target, uint32_t delay) {
        int n = SPIN_LIMIT;
        if (delay) while (elapsed(t_red) < delay) keep();
        bool more;
        do {
            const float4 v = ld_relaxed4(p), v2 = ld_relaxed4(p + 256);
            keep();
            --n;
            more = __any_sync(0xffffffffu, v.w + v2.w != target && n > 0);
            put_x(v.x + v2.x, v.y + v2.y, v.z + v2.z);
        } while (more);
        commit_x();
    };

#pragma unroll
    for (int layer = 0; layer < 2; layer++) {
#pragma unroll
        for (int j = 0; j < 16; j++) ldsm4t(S[j], a_gemv + OFF_WQ + ((j >> 2) * 128 + (j & 3) * 16) * 128);
        if (layer == 0) {
            float c0[4], c1[4];
            zero4(c0); zero4(c1);
#pragma unroll
            for (int j = 0; j < 8; j++) { mma(c0, S[2 * j], ONES, ONES); mma(c1, S[2 * j + 1], ONES, ONES); }
            cs_q = ((c0[0] + c0[3]) + (c1[0] + c1[3])) * (1.f / 512.f);
            put_x(0.f, 0.f, 0.f);
            commit_x();
            if (b < 2 && own) red4(accw, 0.5f * xo[0], 0.5f * xo[1], t < 2 ? 0.5f * xo[2] : 0.f, 1.f);
            xo[0] = xo[1] = xo[2] = 0.f;
        } else {
            if (!ffn) { while (gtime() - g0 < P1NS) keep(); exchange_wait(accp + eoff(0), (float)(NCTA + 2), 0); t_red = elapsed(0) + PDN; if (PDN) while ((int)elapsed(t_red) < 0) keep(); }
            exchange_wait(accp + eoff(1), (float)NFFN, PD2);
        }
        float ls, lq;
        {
            uint4 u0 = lds128(a_row + OFF_XS), u1 = lds128(a_row + OFF_XS + 16);
            float acc[4][4];
#pragma unroll
            for (int a = 0; a < 4; a++) { zero4(acc[a]); mma(acc[a], S[a * 4 + 0], u0.x, u0.y); }
            ln_partials(u0, u1, g & 1, ls, lq);
#pragma unroll
            for (int a = 0; a < 4; a++) mma(acc[a], S[a * 4 + 1], u0.z, u0.w);
#pragma unroll
            for (int a = 0; a < 4; a++) mma(acc[a], S[a * 4 + 2], u1.x, u1.y);
#pragma unroll
            for (int a = 0; a < 4; a++) mma(acc[a], S[a * 4 + 3], u1.z, u1.w);
            float e0 = (t & 2) ? ((t & 1) ? acc[3][0] : acc[2][0]) : ((t & 1) ? acc[1][0] : acc[0][0]);
            float e1 = (t & 2) ? ((t & 1) ? acc[3][3] : acc[2][3]) : ((t & 1) ? acc[1][3] : acc[0][3]);
            float q = fmaf(-ls, cs_q, e0) + e1;
            q += __shfl_xor_sync(0xffffffffu, q, 1);
            q += __shfl_xor_sync(0xffffffffu, q, 2);
            if (t == 0) sts16(a_qo + OFF_QS, pack_bf16(q, 0.f));
        }
        cta_sync();
        if (layer == 0) {
            if (w == 7) { todo = 2; due = (uint32_t)((24 - LEAD) * QNS); }
            gated_wait(bars + B_K, 4, false);
            while (todo) issue(4);
#pragma unroll
            for (int j = 0; j < 16; j++)
                ldsm4(Kf[j], sb + OFF_K + w * 8192 + ((j >> 2) * 16 + (mi & 1) * 8 + li) * 128 + ((((j & 3) * 2 + (mi >> 1)) ^ li) << 4));
        }
        float s0, s1, scl;
        {
            uint4 q0 = lds128(a_t32 + OFF_QS), q1 = lds128(a_t32 + OFF_QS + 16);
            float sc[4][4];
#pragma unroll
            for (int j = 0; j < 4; j++) { zero4(sc[j]); mma(sc[j], Kf[j * 4 + 0], q0.x, q0.y); }
#pragma unroll
            for (int j = 0; j < 4; j++) mma(sc[j], Kf[j * 4 + 1], q0.z, q0.w);
#pragma unroll
            for (int j = 0; j < 4; j++) mma(sc[j], Kf[j * 4 + 2], q1.x, q1.y);
#pragma unroll
            for (int j = 0; j < 4; j++) mma(sc[j], Kf[j * 4 + 3], q1.z, q1.w);
            float mean, rstd;
            ln_finish(ls, lq, mean, rstd);
            scl = rstd * (0.08838834764831845f * 1.4426950408889634f);
            s0 = (t & 2) ? ((t & 1) ? sc[3][0] : sc[2][0]) : ((t & 1) ? sc[1][0] : sc[0][0]);
            s1 = (t & 2) ? ((t & 1) ? sc[3][2] : sc[2][2]) : ((t & 1) ? sc[1][2] : sc[0][2]);
            asm volatile("st.async.weak.shared::cluster.mbarrier::complete_tx::bytes.v2.f32 [%0], {%1,%2}, [%3];"
                         ::"r"(peer_sx + (layer ? OFF_SX1 : OFF_SX0)), "f"(s0), "f"(s1), "r"(peer_bar) : "memory");
            FENCE();
            if (layer == 1) {
#pragma unroll
                for (int j = NWO0; j < NWO1; j++) WO_FRAG(j);
            }
        }
        s0 *= scl; s1 *= scl;
        mbar_wait(a_bsx, layer);
        {
            float2 o2 = lds64f(a_sx + (layer ? OFF_SX1 : OFF_SX0));
            s0 = fmaf(o2.x, scl, s0);
            s1 = fmaf(o2.y, scl, s1);
            int mi_ = __float_as_int(fmaxf(fmaxf(s0, s1), -3.0e38f));
            mi_ ^= (mi_ >> 31) & 0x7fffffff;
            mi_ = __reduce_max_sync(0xffffffffu, mi_);
            mi_ ^= (mi_ >> 31) & 0x7fffffff;
            const float mw = __int_as_float(mi_);
            uint32_t pp = pack_bf16(ex2(s0 - mw), ex2(s1 - mw));
            sts16(a_pst, pp);
            sts16(a_pst + 4, pp >> 16);
            if (lane == 0) sts32f(a_qo + OFF_M, mw);
        }
        cta_sync();
        float M, tot;
        float2 rem, rem2;
        {
            uint4 u0 = lds128(a_row + OFF_PS), u1 = lds128(a_row + OFF_PS + 16);
            float mg = lds32f(a_mg);
            FENCE();
            float4 m0 = lds128f(a_sb + OFF_M), m1 = lds128f(a_sb + OFF_M + 16);
            float2 mt = lds64f(a_mt);
            if (w == 0) {
                float c[4], d[4];
                zero4(c); zero4(d);
                mma_ab(c, u0.x, u0.y, u0.z, u0.w, ONES, ONES);
                mma_ab(d, u1.x, u1.y, u1.z, u1.w, ONES, ONES);
                const float l0 = (c[1] + c[3]) + (d[1] + d[3]);
                if (t == 0) st_relaxed2(mlo + layer, mg, __uint_as_float(__float_as_uint(l0) | 0x80000000u));
                __syncwarp();
            }
            float acc[4][4];
            if (layer == 0) {
                if (lane == 0) mbar_expect(bars + B_SX, 256);
                asm volatile("{\n.reg .pred p;\nsetp.eq.u32 p, %0, 0x7fd3a5c1;\n@p nanosleep.u32 1;\n}" ::"r"(zdep) : "memory");
                todo = 3; due = (uint32_t)((WOQ - LEAD) * QNS + w * (QNS / 2));
#pragma unroll
                for (int a = 0; a < 4; a++) {
                    if (a == 1) rem = ld_relaxed2(mlp);
                    gated_wait(sb + OFF_BAR + a * BS + B_V, 8 | 16, false);
#pragma unroll
                    for (int j = 0; j < 4; j++) ldsm4t(Vf[a * 4 + j], a_gemv + OFF_V + (a * 128 + j * 16) * 128);
                    zero4(acc[a]);
                    mma(acc[a], Vf[a * 4 + 0], u0.x, u0.y);
                    mma(acc[a], Vf[a * 4 + 1], u0.z, u0.w);
                    mma(acc[a], Vf[a * 4 + 2], u1.x, u1.y);
                    mma(acc[a], Vf[a * 4 + 3], u1.z, u1.w);
                }
            } else {
#pragma unroll
                for (int a = 0; a < 4; a++) { zero4(acc[a]); mma(acc[a], Vf[a * 4 + 0], u0.x, u0.y); }
                WO_FRAG(NWO1); WO_FRAG(NWO1 + 1); WO_FRAG(NWO1 + 2); WO_FRAG(NWO1 + 3);
                const uint32_t d0 = __float_as_uint(acc[3][1]);
                m0.x = __uint_as_float(DEP2(__float_as_uint(m0.x), d0, d0)); m0.z = __uint_as_float(DEP2(__float_as_uint(m0.z), d0, d0));
                m1.x = __uint_as_float(DEP2(__float_as_uint(m1.x), d0, d0)); m1.z = __uint_as_float(DEP2(__float_as_uint(m1.z), d0, d0));
#pragma unroll
                for (int a = 0; a < 4; a++) mma(acc[a], Vf[a * 4 + 1], u0.z, u0.w);
#pragma unroll
                for (int a = 0; a < 4; a++) mma(acc[a], Vf[a * 4 + 2], u1.x, u1.y);
                uint32_t bz = DEP2(u1.z, Wf[NWO1][0], Wf[NWO1 + 1][0]), bw = DEP2(u1.w, Wf[NWO1 + 2][0], Wf[NWO1 + 3][0]);
#pragma unroll
                for (int a = 0; a < 4; a++) mma(acc[a], Vf[a * 4 + 3], bz, bw);
            }
            M = fmaxf(fmaxf(fmaxf(m0.x, m0.y), fmaxf(m0.z, m0.w)), fmaxf(fmaxf(m1.x, m1.y), fmaxf(m1.z, m1.w)));
            {
                float c[4];
                zero4(c);
                mma_ab(c, u0.x, u0.y, u0.z, u0.w, ONES, ONES);
                mma_ab(c, u1.x, u1.y, u1.z, u1.w, ONES, ONES);
                tot = (c[0] + c[2]) * ex2(mg - M);
            }
            const float f0 = ex2(mt.x - M), f1 = ex2(mt.y - M);
            float e0 = (t & 2) ? ((t & 1) ? acc[3][0] : acc[2][0]) : ((t & 1) ? acc[1][0] : acc[0][0]);
            float e1 = (t & 2) ? ((t & 1) ? acc[3][3] : acc[2][3]) : ((t & 1) ? acc[1][3] : acc[0][3]);
            float o = fmaf(f0, e0, f1 * e1);
            if (layer == 1) { FENCE(); rem = ld_relaxed2(mlp + 1); }
            o += __shfl_xor_sync(0xffffffffu, o, 1);
            o += __shfl_xor_sync(0xffffffffu, o, 2);
            if (t == 0) sts16(a_qo + OFF_OS, pack_bf16(o, 0.f));
        }
        cta_sync();
        if (layer == 0) {
            if (todo == 3) issue(8);
            if (w >= 4 && ffn) { todo = 5; due = (uint32_t)((F2Q - LEAD) * QNS); }
            gated_wait(bars + B_WO, 16 | 32, true);
#pragma unroll
            for (int j = 0; j < NWO1 + 4; j++) WO_FRAG(j);
        }
        {
            uint4 o0 = lds128(a_t32 + OFF_OS), o1 = lds128(a_t32 + OFF_OS + 16);
#pragma unroll
            for (int j = NWO1 + 4; j < 16; j++) WO_FRAG(j);
            if (layer == 1) rem2 = ld_relaxed2(mlp + 1); else rem2 = rem;
            FENCE();
            float y[4][4];
#pragma unroll
            for (int j = 0; j < 4; j++) { zero4(y[j]); mma(y[j], Wf[j], o0.x, o0.y); }
#pragma unroll
            for (int j = 0; j < 4; j++) mma(y[j], Wf[4 + j], o0.z, o0.w);
#pragma unroll
            for (int j = 0; j < 4; j++) mma(y[j], Wf[8 + j], o1.x, o1.y);
#pragma unroll
            for (int j = 0; j < 4; j++) mma(y[j], Wf[12 + j], o1.z, o1.w);
            FENCE();
            if (!__all_sync(0xffffffffu, __float_as_uint(rem.y) != 0u)) {
                rem = rem2;
                int n = 0;
                while (!__all_sync(0xffffffffu, __float_as_uint(rem.y) != 0u) && ++n < SPIN_LIMIT) rem = ld_relaxed2(mlp + layer);
            }
            tot = fmaf(-rem.y, ex2(rem.x - M), tot);
            tot += __shfl_xor_sync(0xffffffffu, tot, 4);
            tot += __shfl_xor_sync(0xffffffffu, tot, 8);
            tot += __shfl_xor_sync(0xffffffffu, tot, 16);
            const float inv = rcp(tot);
            float v0 = (t == 0) ? y[0][0] : (t == 1) ? y[1][2] : y[3][0];
            float v1 = (t == 0) ? y[0][2] : (t == 1) ? y[2][0] : y[3][2];
            float v2 = (t == 0) ? y[1][0] : (t == 1) ? y[2][2] : 0.f;
            if (own) red4(accw + layer * eoff(2), v0 * inv, v1 * inv, v2 * inv, 1.f);
            t_red = elapsed(0);
            if (layer == 1 && w == 0 && t == 0) st_relaxed2(mlo, 0.f, 0.f);
        }

        if (ffn) {
            const uint32_t a_fst = pin(sb + OFF_FP + (w >> 2) * 256 + ((w & 1) * 8 + g) * 16 + ((w >> 1) & 1) * 8, lane);
            const bool fst = t == (w >> 1);
            const uint32_t a_frd = pin(sb + OFF_FP + (lane & 15) * 16, lane);
            const uint32_t a_w2 = sb + OFF_W2 + w * 2048 + ((mi >> 1) * 8 + li) * 128 + (((mi & 1) ^ li) << 4);
            if (layer == 0) {
                while (todo) { if (gtime() - g0 >= due) issue(16 | 32); keep(); }
            }
            const uint32_t a_w13 = sb + OFF_W13 + (w >> 2) * 16384 + (mi & 1) * 8192 + (((w >> 1) & 1) * 128 + (mi >> 1) * 8 + li) * 32 + (((w & 1) ^ (li >> 2)) << 4);
            auto stage_w13 = [&]() {
#pragma unroll
                for (int j = 0; j < 8; j++) ldsm4t(S[j], a_w13 + j * 16 * 32);
                if (layer == 0) {
                    float c0[4], c1[4];
                    zero4(c0); zero4(c1);
#pragma unroll
                    for (int j = 0; j < 4; j++) { mma(c0, S[2 * j], ONES, ONES); mma(c1, S[2 * j + 1], ONES, ONES); }
                    if (t == 0) asm volatile("st.shared.v2.f32 [%0], {%1,%2};" ::"r"(a_fst + (OFF_FC - OFF_FP)), "f"(c0[0] + c1[0]), "f"(c0[2] + c1[2]) : "memory");
                }
            };
            if (layer == 0) {
                const uint32_t bw1 = sb + OFF_BAR + (w >> 2) * 2 * BS + B_F;
                bool staged = false, more;
                int n = SPIN_LIMIT;
                while (gtime() - g0 < P1NS) {
                    keep();
                    if (!staged && mbar_test(bw1) && mbar_test(bw1 + BS)) { stage_w13(); staged = true; }
                }
                do {
                    const float4 v = ld_relaxed4(accp), v2 = ld_relaxed4(accp + 256);
                    keep();
                    if (!staged && mbar_test(bw1) && mbar_test(bw1 + BS)) { stage_w13(); staged = true; }
                    --n;
                    more = __any_sync(0xffffffffu, v.w + v2.w != (float)(NCTA + 2) && n > 0);
                    put_x(v.x + v2.x, v.y + v2.y, v.z + v2.z);
                } while (more);
                if (!staged) { gated_wait(bw1, 0, true); gated_wait(bw1 + BS, 0, true); stage_w13(); }
                commit_x();
            } else {
                stage_w13();
#pragma unroll
                for (int j = 0; j < 4; j++) ldsm4t(S[8 + j], a_w2 ^ (j << 5));
                exchange_wait(accp + eoff(2), (float)NCTA, PD3);
            }
            {
                uint4 u0 = lds128(a_row + OFF_XS), u1 = lds128(a_row + OFF_XS + 16);
                if (layer == 0) {
                    float4 p0 = lds128f(a_frd + (OFF_FC - OFF_FP)), p1 = lds128f(a_frd + (OFF_FC - OFF_FP) + 256);
                    cs_g = (p0.x + p0.z) + (p1.x + p1.z);
                    cs_u = (p0.y + p0.w) + (p1.y + p1.w);
                }
                {
                    const uint32_t z0 = own ? p01 : 0u, z1 = t < 2 ? p2 : 0u;
                    float c[4];
                    zero4(c);
                    mma_ab(c, z0, ONES, z1, ONES, z0, z1);
                    float s_ = c[2] + c[3], q_ = (g & 1) ? c[1] : c[0];
                    q_ += __shfl_xor_sync(0xffffffffu, q_, 4);
                    s_ += __shfl_xor_sync(0xffffffffu, s_, 1);
                    q_ += __shfl_xor_sync(0xffffffffu, q_, 9);
                    s_ += __shfl_xor_sync(0xffffffffu, s_, 2);
                    q_ += __shfl_xor_sync(0xffffffffu, q_, 18);
                    if (lane == 0) { sts32f(a_qo + OFF_SQ, s_); sts32f(a_qo + OFF_SQ + 32, q_); }
                }
                float acc[4][4];
                zero4(acc[0]); zero4(acc[1]); zero4(acc[2]); zero4(acc[3]);
                mma(acc[0], S[0], u0.x, u0.y); mma(acc[1], S[4], u0.x, u0.y); mma(acc[2], S[2], u1.x, u1.y); mma(acc[3], S[6], u1.x, u1.y);
                mma(acc[0], S[1], u0.z, u0.w); mma(acc[1], S[5], u0.z, u0.w); mma(acc[2], S[3], u1.z, u1.w); mma(acc[3], S[7], u1.z, u1.w);
                if (fst) asm volatile("st.shared.v2.f32 [%0], {%1,%2};" ::"r"(a_fst), "f"((acc[0][0] + acc[2][0]) + (acc[1][1] + acc[3][1])),
                                      "f"((acc[0][2] + acc[2][2]) + (acc[1][3] + acc[3][3])) : "memory");
            }
            cta_sync();
            {
                const float4 s0 = lds128f(a_sb + OFF_SQ), s1 = lds128f(a_sb + OFF_SQ + 16), q0 = lds128f(a_sb + OFF_SQ + 32), q1 = lds128f(a_sb + OFF_SQ + 48);
                float4 p0 = lds128f(a_frd), p1 = lds128f(a_frd + 256);
                const float mean2 = (((s0.x + s0.y) + (s0.z + s0.w)) + ((s1.x + s1.y) + (s1.z + s1.w))) * (1.f / 512.f);
                const float ssq = ((q0.x + q0.y) + (q0.z + q0.w)) + ((q1.x + q1.y) + (q1.z + q1.w));
                const float rstd2 = rsq(fmaxf(fmaf(-mean2, mean2, fmaf(ssq, 1.f / 512.f, 1e-5f)), 1e-5f));
                if (layer == 0) {
                    mbar_wait(sb + OFF_BAR + (4 + (w >> 1)) * BS + B_F, 0);
#pragma unroll
                    for (int j = 0; j < 4; j++) ldsm4t(S[8 + j], a_w2 ^ (j << 5));
                }
                float gate = rstd2 * (fmaf(-mean2, cs_g, p0.x + p0.z) + (p1.x + p1.z));
                float up = rstd2 * (fmaf(-mean2, cs_u, p0.y + p0.w) + (p1.y + p1.w));
                float hv = gate * up * rcp(1.f + ex2(-1.4426950408889634f * gate));
                float h0 = __shfl_sync(0xffffffffu, hv, 2 * t), h1 = __shfl_sync(0xffffffffu, hv, 2 * t + 1);
                float h2 = __shfl_sync(0xffffffffu, hv, 2 * t + 8), h3 = __shfl_sync(0xffffffffu, hv, 2 * t + 9);
                const uint32_t b0 = pack_bf16(h0, h1), b1 = pack_bf16(h2, h3);
                float y[4][4];
#pragma unroll
                for (int j = 0; j < 4; j++) {
                    zero4(y[j]);
                    mma(y[j], S[8 + j], b0, b1);
                }
                float v0 = (t == 0) ? y[0][0] : (t == 1) ? y[1][2] : y[3][0];
                float v1 = (t == 0) ? y[0][2] : (t == 1) ? y[2][0] : y[3][2];
                float v2 = (t == 0) ? y[1][0] : (t == 1) ? y[2][2] : 0.f;
                if (layer == 0) {
                    if (own) red4(accw + eoff(1), v0, v1, v2, 1.f);
                    t_red = elapsed(0);
                } else if (own) {
                    float4 old = atom4(accp + eoff(3) + (g & 1) * 208, v0, v1, v2, 1.f);
                    if (b < 2) st_relaxed4(accw + eoff(0), 0.f, 0.f, 0.f, 0.f);
                    if (old.w == (float)(NFFN - 1)) {
                        const int c = 64 * w + 24 * t + g;
                        out[c] = __float2bfloat16(xo[0] + (old.x + v0));
                        out[c + 8] = __float2bfloat16(xo[1] + (old.y + v1));
                        if (t < 2) out[c + 16] = __float2bfloat16(xo[2] + (old.z + v2));
                    }
                }
            }
        }
    }
}

typedef CUresult (*EncodeFn)(CUtensorMap*, CUtensorMapDataType, cuuint32_t, void*, const cuuint64_t*, const cuuint64_t*,
                             const cuuint32_t*, const cuuint32_t*, CUtensorMapInterleave, CUtensorMapSwizzle,
                             CUtensorMapL2promotion, CUtensorMapFloatOOBfill);

void make_map(EncodeFn enc, CUtensorMap* m, const void* p, uint64_t cols, uint64_t rows, uint32_t bc, uint32_t br) {
    cuuint64_t gd[2] = {cols, rows};
    cuuint64_t gs[1] = {cols * 2};
    cuuint32_t bd[2] = {bc, br};
    cuuint32_t es[2] = {1, 1};
    enc(m, CU_TENSOR_MAP_DATA_TYPE_BFLOAT16, 2, const_cast<void*>(p), gd, gs, bd, es, CU_TENSOR_MAP_INTERLEAVE_NONE,
        bc == 64 ? CU_TENSOR_MAP_SWIZZLE_128B : CU_TENSOR_MAP_SWIZZLE_32B, CU_TENSOR_MAP_L2_PROMOTION_NONE,
        CU_TENSOR_MAP_FLOAT_OOB_FILL_NONE);
}

}

extern "C" void kernel_launch(void* const* d_in, const int* in_sizes, int n_in, void* d_out, int out_size) {
    (void)in_sizes; (void)n_in; (void)out_size;
    static EncodeFn enc = nullptr;
    static unsigned char* acc = nullptr;
    static MlRow* ml = nullptr;
    if (!enc) {
        void* p = nullptr;
        cudaGetSymbolAddress(&p, g_acc_raw);
        acc = reinterpret_cast<unsigned char*>((reinterpret_cast<uintptr_t>(p) + 32767) & ~(uintptr_t)32767);
        cudaGetSymbolAddress(&p, g_ml_buf);
        ml = reinterpret_cast<MlRow*>(p);
        cudaDriverEntryPointQueryResult qr;
        void* fn = nullptr;
        cudaGetDriverEntryPoint("cuTensorMapEncodeTiled", &fn, cudaEnableDefault, &qr);
        enc = (EncodeFn)fn;
        cudaFuncSetAttribute(fused_kernel, cudaFuncAttributeMaxDynamicSharedMemorySize, (int)SMEM_BYTES);
    }
    Maps mp;
    make_map(enc, &mp.wq, d_in[3], 4096, 512, 64, 256);
    make_map(enc, &mp.k, d_in[1], 128, 32 * 4096, 64, 64);
    make_map(enc, &mp.v, d_in[2], 128, 32 * 4096, 64, 64);
    make_map(enc, &mp.wo, d_in[4], 512, 4096, 64, 64);
    make_map(enc, &mp.w1, d_in[6], 1376, 512, 16, 256);
    make_map(enc, &mp.w3, d_in[7], 1376, 512, 16, 256);
    make_map(enc, &mp.w2, d_in[8], 512, 1376, 64, 16);
    fused_kernel<<<NCTA, NTHR, SMEM_BYTES>>>((const __nv_bfloat16*)d_in[0], (__nv_bfloat16*)d_out, acc, ml, mp);
}
```

```cpp
#include <cuda_runtime.h>
#include <cuda_bf16.h>
#include <cuda.h>
#include <stdint.h>

namespace {

constexpr int NCTA = 128;
constexpr int NTHR = 256;
constexpr int NFFN = 86;
constexpr int NWO0 = 3;
constexpr int NWO1 = 8;
constexpr uint32_t PD2 = 500u;
constexpr uint32_t PD3 = 480u;
constexpr uint32_t PDN = 700u;
constexpr int QNS = 155;
constexpr int LEAD = 5;
constexpr int FQ = 46;
constexpr int F2Q = 62;
constexpr int WOQ = 40;
constexpr int RA = 1;
constexpr uint32_t P1NS = 8800u;
constexpr int SPIN_LIMIT = 1 << 20;

constexpr uint32_t OFF_WQ = 0;
constexpr uint32_t OFF_K = 65536;
constexpr uint32_t OFF_W13 = OFF_K + 5 * 8192;
constexpr uint32_t OFF_SX0 = OFF_K + 65536;
constexpr uint32_t OFF_WO5 = OFF_SX0 + 8192;
constexpr uint32_t OFF_V = OFF_WO5 + 24576;
constexpr uint32_t OFF_W2 = OFF_V;
constexpr uint32_t OFF_SX1 = OFF_V + 16384;
constexpr uint32_t OFF_FP = OFF_SX1 + 2048;
constexpr uint32_t OFF_FC = OFF_FP + 512;
constexpr uint32_t VS = 144;
constexpr uint32_t OFF_XS = OFF_V + 65536;
constexpr uint32_t OFF_PS = OFF_XS + 1152;
constexpr uint32_t OFF_QS = OFF_PS + 1152;
constexpr uint32_t OFF_OS = OFF_QS + 128;
constexpr uint32_t OFF_M = OFF_OS + 128;
constexpr uint32_t OFF_SQ = OFF_M + 32;
constexpr uint32_t OFF_BAR = OFF_SQ + 64;
constexpr uint32_t BS = 48;
constexpr uint32_t B_WQ = 0, B_K = 8, B_V = 16, B_WO = 24, B_F = 32, B_SX = 40;
constexpr uint32_t SMEM_BYTES = OFF_BAR + 8 * BS;
static_assert(SMEM_BYTES <= 232448, "smem");

struct Maps { CUtensorMap wq, k, v, wo, w1, w3, w2; };

typedef float2 MlRow[NCTA][16];
__device__ __align__(128) unsigned char g_acc_raw[65536];
__device__ __align__(128) float2 g_ml_buf[1][NCTA][16];

__device__ __forceinline__ void mbar_init(uint32_t a, int c) {
    asm volatile("mbarrier.init.shared::cta.b64 [%0], %1;" ::"r"(a), "r"(c) : "memory");
}
__device__ __forceinline__ void mbar_expect(uint32_t a, uint32_t bytes) {
    asm volatile("mbarrier.arrive.expect_tx.shared::cta.b64 _, [%0], %1;" ::"r"(a), "r"(bytes) : "memory");
}
__device__ __forceinline__ void mbar_wait(uint32_t a, uint32_t parity) {
    uint32_t ok;
    int n = 0;
    do {
        asm volatile("{\n.reg .pred p;\nmbarrier.try_wait.parity.shared::cta.b64 p, [%1], %2;\nselp.u32 %0, 1, 0, p;\n}"
                     : "=r"(ok) : "r"(a), "r"(parity) : "memory");
    } while (!ok && ++n < SPIN_LIMIT);
}
__device__ __forceinline__ bool mbar_test(uint32_t a) {
    uint32_t ok;
    asm volatile("{\n.reg .pred p;\nmbarrier.test_wait.parity.shared::cta.b64 p, [%1], 0;\nselp.u32 %0, 1, 0, p;\n}" : "=r"(ok) : "r"(a) : "memory");
    return ok;
}
__device__ __forceinline__ uint32_t gtime() {
    uint32_t c;
    asm volatile("mov.u32 %0, %%globaltimer_lo;" : "=r"(c) :: "memory");
    return __shfl_sync(0xffffffffu, c, 0);
}
__device__ __forceinline__ void tma2d(uint32_t dst, const CUtensorMap* m, int c0, int c1, uint32_t bar) {
    asm volatile("cp.async.bulk.tensor.2d.shared::cluster.global.mbarrier::complete_tx::bytes [%0], [%1, {%3, %4}], [%2];"
                 ::"r"(dst), "l"(m), "r"(bar), "r"(c0), "r"(c1) : "memory");
}
__device__ __forceinline__ void tma2d_stream(uint32_t dst, const CUtensorMap* m, int c0, int c1, uint32_t bar) {
    asm volatile("{\n.reg .b64 pol;\ncreatepolicy.fractional.L2::evict_first.b64 pol, 1.0;\n"
                 "cp.async.bulk.tensor.2d.shared::cluster.global.mbarrier::complete_tx::bytes.L2::cache_hint [%0], [%1, {%3, %4}], [%2], pol;\n}"
                 ::"r"(dst), "l"(m), "r"(bar), "r"(c0), "r"(c1) : "memory");
}
__device__ __forceinline__ void ldsm4(uint32_t* r, uint32_t a) {
    asm volatile("ldmatrix.sync.aligned.m8n8.x4.shared.b16 {%0,%1,%2,%3}, [%4];"
                 : "=r"(r[0]), "=r"(r[1]), "=r"(r[2]), "=r"(r[3]) : "r"(a) : "memory");
}
__device__ __forceinline__ void ldsm4t(uint32_t* r, uint32_t a) {
    asm volatile("ldmatrix.sync.aligned.m8n8.x4.trans.shared.b16 {%0,%1,%2,%3}, [%4];"
                 : "=r"(r[0]), "=r"(r[1]), "=r"(r[2]), "=r"(r[3]) : "r"(a) : "memory");
}
__device__ __forceinline__ void mma(float* c, const uint32_t* a, uint32_t b0, uint32_t b1) {
    asm("mma.sync.aligned.m16n8k16.row.col.f32.bf16.bf16.f32 {%0,%1,%2,%3},{%4,%5,%6,%7},{%8,%9},{%0,%1,%2,%3};"
        : "+f"(c[0]), "+f"(c[1]), "+f"(c[2]), "+f"(c[3])
        : "r"(a[0]), "r"(a[1]), "r"(a[2]), "r"(a[3]), "r"(b0), "r"(b1));
}
__device__ __forceinline__ uint4 lds128(uint32_t a) {
    uint4 v;
    asm volatile("ld.shared.v4.u32 {%0,%1,%2,%3}, [%4];" : "=r"(v.x), "=r"(v.y), "=r"(v.z), "=r"(v.w) : "r"(a) : "memory");
    return v;
}
__device__ __forceinline__ float4 lds128f(uint32_t a) {
    float4 v;
    asm volatile("ld.shared.v4.f32 {%0,%1,%2,%3}, [%4];" : "=f"(v.x), "=f"(v.y), "=f"(v.z), "=f"(v.w) : "r"(a) : "memory");
    return v;
}
__device__ __forceinline__ float2 lds64f(uint32_t a) {
    float2 v;
    asm volatile("ld.shared.v2.f32 {%0,%1}, [%2];" : "=f"(v.x), "=f"(v.y) : "r"(a) : "memory");
    return v;
}
__device__ __forceinline__ float lds32f(uint32_t a) {
    float v;
    asm volatile("ld.shared.f32 %0, [%1];" : "=f"(v) : "r"(a) : "memory");
    return v;
}
__device__ __forceinline__ void sts16(uint32_t a, uint32_t v) {
    asm volatile("st.shared.u16 [%0], %1;" ::"r"(a), "h"((unsigned short)v) : "memory");
}
__device__ __forceinline__ void sts32f(uint32_t a, float v) {
    asm volatile("st.shared.f32 [%0], %1;" ::"r"(a), "f"(v) : "memory");
}
__device__ __forceinline__ void cta_sync() { asm volatile("bar.sync 0;" ::: "memory"); }
__device__ __forceinline__ float ex2(float x) {
    float y;
    asm("ex2.approx.ftz.f32 %0, %1;" : "=f"(y) : "f"(x));
    return y;
}
__device__ __forceinline__ float rcp(float x) {
    float y;
    asm("rcp.approx.ftz.f32 %0, %1;" : "=f"(y) : "f"(x));
    return y;
}
__device__ __forceinline__ uint32_t pack_bf16(float lo, float hi) {
    uint32_t r;
    asm("cvt.rn.bf16x2.f32 %0, %1, %2;" : "=r"(r) : "f"(hi), "f"(lo));
    return r;
}
__device__ __forceinline__ float4 ld_relaxed4(const void* p) {
    float4 v;
    asm volatile("ld.relaxed.gpu.global.v4.f32 {%0,%1,%2,%3}, [%4];" : "=f"(v.x), "=f"(v.y), "=f"(v.z), "=f"(v.w) : "l"(p) : "memory");
    return v;
}
__device__ __forceinline__ float2 ld_relaxed2(const void* p) {
    float2 v;
    asm volatile("ld.relaxed.gpu.global.v2.f32 {%0,%1}, [%2];" : "=f"(v.x), "=f"(v.y) : "l"(p) : "memory");
    return v;
}
__device__ __forceinline__ void st_relaxed2(void* p, float x, float y) {
    asm volatile("st.relaxed.gpu.global.v2.f32 [%0], {%1,%2};" ::"l"(p), "f"(x), "f"(y) : "memory");
}
__device__ __forceinline__ void st_relaxed4(void* p, float x, float y, float z, float w) {
    asm volatile("st.relaxed.gpu.global.v4.f32 [%0], {%1,%2,%3,%4};" ::"l"(p), "f"(x), "f"(y), "f"(z), "f"(w) : "memory");
}
__device__ __forceinline__ void red4(void* p, float x, float y, float z, float w) {
    asm volatile("red.relaxed.gpu.global.add.v4.f32 [%0], {%1,%2,%3,%4};" ::"l"(p), "f"(x), "f"(y), "f"(z), "f"(w) : "memory");
}
__device__ __forceinline__ float4 atom4(void* p, float x, float y, float z, float w) {
    float4 v;
    asm volatile("atom.relaxed.gpu.global.add.v4.f32 {%0,%1,%2,%3}, [%4], {%5,%6,%7,%8};"
                 : "=f"(v.x), "=f"(v.y), "=f"(v.z), "=f"(v.w) : "l"(p), "f"(x), "f"(y), "f"(z), "f"(w) : "memory");
    return v;
}
__device__ __forceinline__ constexpr uint32_t eoff(int e) { return (uint32_t)((e & 1) * 128 + (e >> 1) * 512); }

constexpr uint32_t ONES = 0x3F803F80u;

__device__ __forceinline__ void mma_ab(float* c, uint32_t a0, uint32_t a1, uint32_t a2, uint32_t a3, uint32_t b0, uint32_t b1) {
    asm("mma.sync.aligned.m16n8k16.row.col.f32.bf16.bf16.f32 {%0,%1,%2,%3},{%4,%5,%6,%7},{%8,%9},{%0,%1,%2,%3};"
        : "+f"(c[0]), "+f"(c[1]), "+f"(c[2]), "+f"(c[3])
        : "r"(a0), "r"(a1), "r"(a2), "r"(a3), "r"(b0), "r"(b1));
}
__device__ __forceinline__ bool elect_one() {
    uint32_t p;
    asm volatile("{\n.reg .pred p;\nelect.sync _|p, 0xffffffff;\nselp.u32 %0, 1, 0, p;\n}" : "=r"(p));
    return p;
}
__device__ __forceinline__ float rsq(float x) {
    float y;
    asm("rsqrt.approx.ftz.f32 %0, %1;" : "=f"(y) : "f"(x));
    return y;
}
__device__ __forceinline__ uint32_t elapsed(uint32_t c0) {
    uint32_t c;
    asm volatile("mov.u32 %0, %%clock;" : "=r"(c) :: "memory");
    return __shfl_sync(0xffffffffu, c, 0) - c0 ;
}
__device__ __forceinline__ void zero4(float* c) { c[0] = c[1] = c[2] = c[3] = 0.f; }
__device__ __forceinline__ uint32_t pin(uint32_t v, int lane) { return __shfl_sync(0xffffffffu, v, lane); }

__device__ __forceinline__ void ln_partials(const uint4& u0, const uint4& u1, bool godd, float& s, float& q) {
    float c[4], d[4];
    zero4(c); zero4(d);
    mma_ab(c, u0.x, ONES, u0.y, ONES, u0.x, u0.y);
    mma_ab(d, u1.x, ONES, u1.y, ONES, u1.x, u1.y);
    mma_ab(c, u0.z, ONES, u0.w, ONES, u0.z, u0.w);
    mma_ab(d, u1.z, ONES, u1.w, ONES, u1.z, u1.w);
    s = (c[2] + d[2]) + (c[3] + d[3]);
    q = godd ? c[1] + d[1] : c[0] + d[0];
}
__device__ __forceinline__ void ln_finish(float s, float q, float& mean, float& rstd) {
    q += __shfl_xor_sync(0xffffffffu, q, 4);
    s += __shfl_xor_sync(0xffffffffu, s, 1);
    q += __shfl_xor_sync(0xffffffffu, q, 9);
    s += __shfl_xor_sync(0xffffffffu, s, 2);
    q += __shfl_xor_sync(0xffffffffu, q, 18);
    mean = s * (1.f / 512.f);
    q = __shfl_sync(0xffffffffu, q, 0);
    rstd = rsq(fmaxf(fmaf(-mean, mean, q * (1.f / 512.f)), 0.f) + 1e-5f);
}

#define FENCE() __syncwarp()
#define DEP2(x, d1, d2) ((x) | (((d1) | (d2)) & zr))
#define WO_FRAG(j) ldsm4t(Wf[j], (a_wo ^ (((j) & 3) << 5)) + ((j) >> 2) * 2048)

__global__ void __cluster_dims__(2, 1, 1) __launch_bounds__(NTHR, 1)
fused_kernel(const __nv_bfloat16* __restrict__ x_in, __nv_bfloat16* __restrict__ out, unsigned char* const acc_base, MlRow* const g_ml,
             const __grid_constant__ Maps mp) {
    extern __shared__ __align__(1024) unsigned char smem[];
    const uint32_t sb = (uint32_t)__cvta_generic_to_shared(smem);
    const int tid = threadIdx.x;
    const int b = blockIdx.x, r = b & 1, pr = (b >> 1) & 1, h = b >> 2;
    if (tid == 0) {
        mbar_init(sb + OFF_BAR + B_WQ, 1);
        asm volatile("fence.mbarrier_init.release.cluster;" ::: "memory");
        mbar_expect(sb + OFF_BAR + B_WQ, 65536 + 1024);
        asm volatile("cp.async.bulk.shared::cluster.global.mbarrier::complete_tx::bytes [%0], [%1], 1024, [%2];"
                     ::"r"(sb + OFF_PS), "l"(x_in), "r"(sb + OFF_BAR + B_WQ) : "memory");
        tma2d(sb + OFF_WQ, &mp.wq, h * 128 + r * 64, 0, sb + OFF_BAR + B_WQ);
        tma2d(sb + OFF_WQ + 32768, &mp.wq, h * 128 + r * 64, 256, sb + OFF_BAR + B_WQ);
    }
    const uint32_t g0 = gtime();
    const int w = __shfl_sync(0xffffffffu, tid >> 5, 0), lane = tid & 31, g = lane >> 2, t = lane & 3;
    const bool ffn = b < NFFN;
    const uint32_t bars = sb + OFF_BAR + w * BS;
    if (elect_one()) {
        if (w >= 1 && w < 7) asm volatile("prefetch.tensormap [%0];" ::"l"(&mp.wq + w) : "memory");
        mbar_init(bars + B_K, 1); mbar_init(bars + B_V, 1); mbar_init(bars + B_WO, 1); mbar_init(bars + B_F, 1); mbar_init(bars + B_SX, 1);
        asm volatile("fence.mbarrier_init.release.cluster;" ::: "memory");
        mbar_expect(bars + B_SX, 256);
    }
    __syncwarp();
    asm volatile("barrier.cluster.arrive.relaxed.aligned;" ::: "memory");

    unsigned char* const accp = acc_base + pin(w * 4096 + (g >> 1) * 1024 + ((g & 1) * 3 + (t < 3 ? t : 2)) * 16, lane);
    unsigned char* const accw = accp + r * 256;
    const bool own = t < 3;
    uint32_t zdep = 0;
    {
        const int z = tid - 32;
        unsigned char* zp;
        if (z < 16) zp = reinterpret_cast<unsigned char*>(&g_ml[0][b][0]) + (z >> 1) * 16 + 8 + (z & 1) * 4;
        else {
            const int i = b * 48 + (z - 16), e = 1 + (i >> 11), u = (i >> 5) & 63;
            zp = acc_base + (u >> 3) * 4096 + (u & 1) * 256 + ((u >> 1) & 3) * 1024 + (e & 1) * 128 + (e >> 1) * 512 + (i & 31) * 4;
        }
        asm volatile("{\n.reg .pred p;\nsetp.lt.u32 p, %2, 64;\n@p atom.relaxed.gpu.global.exch.b32 %0, [%1], 0;\n}"
                     : "+r"(zdep) : "l"(zp), "r"(z) : "memory");
    }

    const int mi = lane >> 3, li = lane & 7;
    const uint32_t wo_box = sb + (w < 5 ? OFF_K + w * 8192 : OFF_WO5 + (w - 5) * 8192);
    const uint32_t a_gemv = pin(sb + ((mi & 1) * 64 + (mi >> 1) * 8 + li) * 128 + ((w ^ li) << 4), lane);
    const uint32_t a_wo = pin(wo_box + ((mi >> 1) * 8 + li) * 128 + (((mi & 1) ^ li) << 4), lane);
    const uint32_t a_xst = pin(sb + OFF_XS + w * VS + (g >> 1) * 32 + (g & 1) * 2 + t * 12, lane);
    const uint32_t a_pst = pin(sb + OFF_PS + w * VS + (g >> 1) * 32 + (g & 1) * 2 + t * 8, lane);
    const uint32_t a_row = pin(sb + g * VS + t * 32, lane);
    const uint32_t a_qo = pin(sb + (g >> 1) * 32 + w * 4 + (g & 1) * 2, lane);
    const uint32_t a_t32 = pin(sb + t * 32, lane);
    const uint32_t a_sx = pin(sb + tid * 8, lane);
    uint32_t peer_sx, peer_bar;
    asm volatile("mapa.shared::cluster.u32 %0, %1, %2;" : "=r"(peer_sx) : "r"(a_sx), "r"(r ^ 1));
    asm volatile("mapa.shared::cluster.u32 %0, %1, %2;" : "=r"(peer_bar) : "r"(bars + B_SX), "r"(r ^ 1));
    const float2* const mlp = &g_ml[0][0][0] + pin((b ^ 2) * 16 + 2 * g, lane);
    float2* const mlo = &g_ml[0][0][0] + pin(b * 16 + 2 * g, lane);
    const uint32_t a_mg = pin(sb + OFF_M + g * 4, lane), a_mt = pin(sb + OFF_M + t * 8, lane), a_sb = pin(sb, lane), a_bsx = pin(bars + B_SX, lane);
    const uint32_t zr = pin(tid >> 20, lane);


    int todo = 1, vi = 0;
    uint32_t due = (uint32_t)((8 + 2 * w - LEAD) * QNS);
    const int kr = h * 4096 + 3072 + pr * 512;
    auto issue = [&](int mask) {
        const bool el = elect_one();
        if ((mask & 2) && todo == 1) {
            if (el) { mbar_expect(bars + B_K, 8192); tma2d_stream(sb + OFF_K + w * 8192, &mp.k, r * 64, kr + w * 64, bars + B_K); }
            todo = 0;
        } else if ((mask & 4) && todo == 2) {
            if (el) {
                const uint32_t bar = sb + OFF_BAR + (vi >> 1) * BS + B_V;
                if (!(vi & 1)) mbar_expect(bar, 16384);
                tma2d_stream(sb + OFF_V + vi * 8192, &mp.v, r * 64, kr + vi * 64, bar);
            }
            vi++; due += 2 * QNS;
            if (vi == 8) todo = 0;
        } else if ((mask & 8) && todo == 3) {
            if (el) { mbar_expect(bars + B_WO, 8192); tma2d(wo_box, &mp.wo, w * 64, h * 128 + r * 64, bars + B_WO); }
            todo = (ffn && w < 4) ? 4 : 0;
            due = (uint32_t)((FQ - LEAD) * QNS + w * (4 * QNS / 3));
        } else if ((mask & 16) && todo == 4) {
            if (el) { mbar_expect(bars + B_F, 8192); tma2d(sb + OFF_W13 + w * 8192, (w & 1) ? &mp.w3 : &mp.w1, b * 16, (w >> 1) * 256, bars + B_F); }
            todo = 0;
        } else if (mask & 32) {
            if (el) {
                mbar_expect(bars + B_F, 4096);
                tma2d(sb + OFF_W2 + (w - 4) * 4096, &mp.w2, (w - 4) * 128, b * 16, bars + B_F);
                tma2d(sb + OFF_W2 + (w - 4) * 4096 + 2048, &mp.w2, (w - 4) * 128 + 64, b * 16, bars + B_F);
            }
            todo = 0;
        }
        __syncwarp();
    };
    uint32_t ka0 = zr, ka1 = zr;
    auto keep = [&]() {
        if (w == 7) asm volatile("mma.sync.aligned.m16n8k8.row.col.f16.f16.f16.f16 {%0,%1},{%2,%2},{%2},{%0,%1};" : "+r"(ka0), "+r"(ka1) : "r"(zr));
    };
    auto gated_wait = [&](uint32_t bar, int mask, bool ka) {
        int n = SPIN_LIMIT << 4;
        while (!mbar_test(bar) && --n > 0) {
            if (mask && todo && gtime() - g0 >= due) issue(mask);
            if (ka) keep();
            if (!todo && (!ka || w != 7)) { mbar_wait(bar, 0); break; }
        }
    };
    uint32_t Kf[16][4], Vf[16][4], S[16][4], Wf[16][4];
    float cs_q = 0.f, cs_g = 0.f, cs_u = 0.f;
    asm volatile("barrier.cluster.wait.acquire.aligned;" ::: "memory");
    gated_wait(sb + OFF_BAR + B_WQ, 2, false);
    if (todo) issue(2);
    float xo[3];
#pragma unroll
    for (int i = 0; i < 3; i++) {
        uint32_t xr;
        asm volatile("ld.shared.u16 %0, [%1];" : "=r"(xr) : "r"(sb + OFF_PS + (64 * w + 8 * ((3 * t + i) & 7) + g) * 2) : "memory");
        xo[i] = __uint_as_float(xr << 16);
    }

    uint32_t p01 = 0, p2 = 0;
    auto put_x = [&](float vx, float vy, float vz) {
        p01 = pack_bf16(xo[0] + vx, xo[1] + vy);
        p2 = pack_bf16(xo[2] + vz, 0.f);
        if (own) { sts16(a_xst, p01); sts16(a_xst + 4, p01 >> 16); }
        if (t < 2) sts16(a_xst + 8, p2);
    };
    auto commit_x = [&]() {
        cta_sync();
        p2 |= ka0 & ka1 & 0xffffu;
        xo[0] = __uint_as_float(p01 << 16); xo[1] = __uint_as_float(p01 & 0xffff0000u); xo[2] = __uint_as_float(p2 << 16);
    };
    uint32_t t_red = 0;
    auto exchange_wait = [&](const unsigned char* p, float target, uint32_t delay) {
        int n = SPIN_LIMIT;
        if (delay) while (elapsed(t_red) < delay) keep();
        bool more;
        do {
            const float4 v = ld_relaxed4(p), v2 = ld_relaxed4(p + 256);
            keep();
            --n;
            more = __any_sync(0xffffffffu, v.w + v2.w != target && n > 0);
            put_x(v.x + v2.x, v.y + v2.y, v.z + v2.z);
        } while (more);
        commit_x();
    };

#pragma unroll
    for (int layer = 0; layer < 2; layer++) {
#pragma unroll
        for (int j = 0; j < 16; j++) ldsm4t(S[j], a_gemv + OFF_WQ + ((j >> 2) * 128 + (j & 3) * 16) * 128);
        if (layer == 0) {
            float c0[4], c1[4];
            zero4(c0); zero4(c1);
#pragma unroll
            for (int j = 0; j < 8; j++) { mma(c0, S[2 * j], ONES, ONES); mma(c1, S[2 * j + 1], ONES, ONES); }
            cs_q = ((c0[0] + c0[3]) + (c1[0] + c1[3])) * (1.f / 512.f);
            put_x(0.f, 0.f, 0.f);
            commit_x();
            if (b < 2 && own) red4(accw, 0.5f * xo[0], 0.5f * xo[1], t < 2 ? 0.5f * xo[2] : 0.f, 1.f);
            xo[0] = xo[1] = xo[2] = 0.f;
        } else {
            if (!ffn) { while (gtime() - g0 < P1NS) keep(); exchange_wait(accp + eoff(0), (float)(NCTA + 2), 0); t_red = elapsed(0) + PDN; if (PDN) while ((int)elapsed(t_red) < 0) keep(); }
            exchange_wait(accp + eoff(1), (float)NFFN, PD2);
        }
        float ls, lq;
        {
            uint4 u0 = lds128(a_row + OFF_XS), u1 = lds128(a_row + OFF_XS + 16);
            float acc[4][4];
#pragma unroll
            for (int a = 0; a < 4; a++) { zero4(acc[a]); mma(acc[a], S[a * 4 + 0], u0.x, u0.y); }
            ln_partials(u0, u1, g & 1, ls, lq);
#pragma unroll
            for (int a = 0; a < 4; a++) mma(acc[a], S[a * 4 + 1], u0.z, u0.w);
#pragma unroll
            for (int a = 0; a < 4; a++) mma(acc[a], S[a * 4 + 2], u1.x, u1.y);
#pragma unroll
            for (int a = 0; a < 4; a++) mma(acc[a], S[a * 4 + 3], u1.z, u1.w);
            float e0 = (t & 2) ? ((t & 1) ? acc[3][0] : acc[2][0]) : ((t & 1) ? acc[1][0] : acc[0][0]);
            float e1 = (t & 2) ? ((t & 1) ? acc[3][3] : acc[2][3]) : ((t & 1) ? acc[1][3] : acc[0][3]);
            float q = fmaf(-ls, cs_q, e0) + e1;
            q += __shfl_xor_sync(0xffffffffu, q, 1);
            q += __shfl_xor_sync(0xffffffffu, q, 2);
            if (t == 0) sts16(a_qo + OFF_QS, pack_bf16(q, 0.f));
        }
        cta_sync();
        if (layer == 0) {
            if (w == 7) { todo = 2; due = (uint32_t)((24 - LEAD) * QNS); }
            gated_wait(bars + B_K, 4, false);
            while (todo) issue(4);
#pragma unroll
            for (int j = 0; j < 16; j++)
                ldsm4(Kf[j], sb + OFF_K + w * 8192 + ((j >> 2) * 16 + (mi & 1) * 8 + li) * 128 + ((((j & 3) * 2 + (mi >> 1)) ^ li) << 4));
        }
        float s0, s1, scl;
        {
            uint4 q0 = lds128(a_t32 + OFF_QS), q1 = lds128(a_t32 + OFF_QS + 16);
            float sc[4][4];
#pragma unroll
            for (int j = 0; j < 4; j++) { zero4(sc[j]); mma(sc[j], Kf[j * 4 + 0], q0.x, q0.y); }
#pragma unroll
            for (int j = 0; j < 4; j++) mma(sc[j], Kf[j * 4 + 1], q0.z, q0.w);
#pragma unroll
            for (int j = 0; j < 4; j++) mma(sc[j], Kf[j * 4 + 2], q1.x, q1.y);
#pragma unroll
            for (int j = 0; j < 4; j++) mma(sc[j], Kf[j * 4 + 3], q1.z, q1.w);
            float mean, rstd;
            ln_finish(ls, lq, mean, rstd);
            scl = rstd * (0.08838834764831845f * 1.4426950408889634f);
            s0 = (t & 2) ? ((t & 1) ? sc[3][0] : sc[2][0]) : ((t & 1) ? sc[1][0] : sc[0][0]);
            s1 = (t & 2) ? ((t & 1) ? sc[3][2] : sc[2][2]) : ((t & 1) ? sc[1][2] : sc[0][2]);
            asm volatile("st.async.weak.shared::cluster.mbarrier::complete_tx::bytes.v2.f32 [%0], {%1,%2}, [%3];"
                         ::"r"(peer_sx + (layer ? OFF_SX1 : OFF_SX0)), "f"(s0), "f"(s1), "r"(peer_bar) : "memory");
            FENCE();
            if (layer == 1) {
#pragma unroll
                for (int j = NWO0; j < NWO1; j++) WO_FRAG(j);
            }
        }
        s0 *= scl; s1 *= scl;
        mbar_wait(a_bsx, layer);
        {
            float2 o2 = lds64f(a_sx + (layer ? OFF_SX1 : OFF_SX0));
            s0 = fmaf(o2.x, scl, s0);
            s1 = fmaf(o2.y, scl, s1);
            int mi_ = __float_as_int(fmaxf(fmaxf(s0, s1), -3.0e38f));
            mi_ ^= (mi_ >> 31) & 0x7fffffff;
            mi_ = __reduce_max_sync(0xffffffffu, mi_);
            mi_ ^= (mi_ >> 31) & 0x7fffffff;
            const float mw = __int_as_float(mi_);
            uint32_t pp = pack_bf16(ex2(s0 - mw), ex2(s1 - mw));
            sts16(a_pst, pp);
            sts16(a_pst + 4, pp >> 16);
            if (lane == 0) sts32f(a_qo + OFF_M, mw);
        }
        cta_sync();
        float M, tot;
        float2 rem, rem2;
        {
            uint4 u0 = lds128(a_row + OFF_PS), u1 = lds128(a_row + OFF_PS + 16);
            float mg = lds32f(a_mg);
            FENCE();
            float4 m0 = lds128f(a_sb + OFF_M), m1 = lds128f(a_sb + OFF_M + 16);
            float2 mt = lds64f(a_mt);
            if (w == 0) {
                float c[4], d[4];
                zero4(c); zero4(d);
                mma_ab(c, u0.x, u0.y, u0.z, u0.w, ONES, ONES);
                mma_ab(d, u1.x, u1.y, u1.z, u1.w, ONES, ONES);
                const float l0 = (c[1] + c[3]) + (d[1] + d[3]);
                if (t == 0) st_relaxed2(mlo + layer, mg, __uint_as_float(__float_as_uint(l0) | 0x80000000u));
                __syncwarp();
            }
            float acc[4][4];
            if (layer == 0) {
                if (lane == 0) mbar_expect(bars + B_SX, 256);
                asm volatile("{\n.reg .pred p;\nsetp.eq.u32 p, %0, 0x7fd3a5c1;\n@p nanosleep.u32 1;\n}" ::"r"(zdep) : "memory");
                todo = 3; due = (uint32_t)((WOQ - LEAD) * QNS + w * (QNS / 2));
#pragma unroll
                for (int a = 0; a < 4; a++) {
                    if (a == RA) rem = ld_relaxed2(mlp);
                    gated_wait(sb + OFF_BAR + a * BS + B_V, 8 | 16, false);
#pragma unroll
                    for (int j = 0; j < 4; j++) ldsm4t(Vf[a * 4 + j], a_gemv + OFF_V + (a * 128 + j * 16) * 128);
                    zero4(acc[a]);
                    mma(acc[a], Vf[a * 4 + 0], u0.x, u0.y);
                    mma(acc[a], Vf[a * 4 + 1], u0.z, u0.w);
                    mma(acc[a], Vf[a * 4 + 2], u1.x, u1.y);
                    mma(acc[a], Vf[a * 4 + 3], u1.z, u1.w);
                }
            } else {
#pragma unroll
                for (int a = 0; a < 4; a++) { zero4(acc[a]); mma(acc[a], Vf[a * 4 + 0], u0.x, u0.y); }
                WO_FRAG(NWO1); WO_FRAG(NWO1 + 1); WO_FRAG(NWO1 + 2); WO_FRAG(NWO1 + 3);
                const uint32_t d0 = __float_as_uint(acc[3][1]);
                m0.x = __uint_as_float(DEP2(__float_as_uint(m0.x), d0, d0)); m0.z = __uint_as_float(DEP2(__float_as_uint(m0.z), d0, d0));
                m1.x = __uint_as_float(DEP2(__float_as_uint(m1.x), d0, d0)); m1.z = __uint_as_float(DEP2(__float_as_uint(m1.z), d0, d0));
#pragma unroll
                for (int a = 0; a < 4; a++) mma(acc[a], Vf[a * 4 + 1], u0.z, u0.w);
#pragma unroll
                for (int a = 0; a < 4; a++) mma(acc[a], Vf[a * 4 + 2], u1.x, u1.y);
                uint32_t bz = DEP2(u1.z, Wf[NWO1][0], Wf[NWO1 + 1][0]), bw = DEP2(u1.w, Wf[NWO1 + 2][0], Wf[NWO1 + 3][0]);
#pragma unroll
                for (int a = 0; a < 4; a++) mma(acc[a], Vf[a * 4 + 3], bz, bw);
            }
            M = fmaxf(fmaxf(fmaxf(m0.x, m0.y), fmaxf(m0.z, m0.w)), fmaxf(fmaxf(m1.x, m1.y), fmaxf(m1.z, m1.w)));
            {
                float c[4];
                zero4(c);
                mma_ab(c, u0.x, u0.y, u0.z, u0.w, ONES, ONES);
                mma_ab(c, u1.x, u1.y, u1.z, u1.w, ONES, ONES);
                tot = (c[0] + c[2]) * ex2(mg - M);
            }
            const float f0 = ex2(mt.x - M), f1 = ex2(mt.y - M);
            float e0 = (t & 2) ? ((t & 1) ? acc[3][0] : acc[2][0]) : ((t & 1) ? acc[1][0] : acc[0][0]);
            float e1 = (t & 2) ? ((t & 1) ? acc[3][3] : acc[2][3]) : ((t & 1) ? acc[1][3] : acc[0][3]);
            float o = fmaf(f0, e0, f1 * e1);
            if (layer == 1) { FENCE(); rem = ld_relaxed2(mlp + 1); }
            o += __shfl_xor_sync(0xffffffffu, o, 1);
            o += __shfl_xor_sync(0xffffffffu, o, 2);
            if (t == 0) sts16(a_qo + OFF_OS, pack_bf16(o, 0.f));
        }
        cta_sync();
        if (layer == 0) {
            if (todo == 3) issue(8);
            if (w >= 4 && ffn) { todo = 5; due = (uint32_t)((F2Q - LEAD) * QNS); }
            gated_wait(bars + B_WO, 16 | 32, true);
#pragma unroll
            for (int j = 0; j < NWO1 + 4; j++) WO_FRAG(j);
        }
        {
            uint4 o0 = lds128(a_t32 + OFF_OS), o1 = lds128(a_t32 + OFF_OS + 16);
#pragma unroll
            for (int j = NWO1 + 4; j < 16; j++) WO_FRAG(j);
            if (layer == 1) rem2 = ld_relaxed2(mlp + 1); else rem2 = rem;
            FENCE();
            float y[4][4];
#pragma unroll
            for (int j = 0; j < 4; j++) { zero4(y[j]); mma(y[j], Wf[j], o0.x, o0.y); }
#pragma unroll
            for (int j = 0; j < 4; j++) mma(y[j], Wf[4 + j], o0.z, o0.w);
#pragma unroll
            for (int j = 0; j < 4; j++) mma(y[j], Wf[8 + j], o1.x, o1.y);
#pragma unroll
            for (int j = 0; j < 4; j++) mma(y[j], Wf[12 + j], o1.z, o1.w);
            FENCE();
            if (!__all_sync(0xffffffffu, __float_as_uint(rem.y) != 0u)) {
                rem = rem2;
                int n = 0;
                while (!__all_sync(0xffffffffu, __float_as_uint(rem.y) != 0u) && ++n < SPIN_LIMIT) rem = ld_relaxed2(mlp + layer);
            }
            tot = fmaf(-rem.y, ex2(rem.x - M), tot);
            tot += __shfl_xor_sync(0xffffffffu, tot, 4);
            tot += __shfl_xor_sync(0xffffffffu, tot, 8);
            tot += __shfl_xor_sync(0xffffffffu, tot, 16);
            const float inv = rcp(tot);
            float v0 = (t == 0) ? y[0][0] : (t == 1) ? y[1][2] : y[3][0];
            float v1 = (t == 0) ? y[0][2] : (t == 1) ? y[2][0] : y[3][2];
            float v2 = (t == 0) ? y[1][0] : (t == 1) ? y[2][2] : 0.f;
            if (own) red4(accw + layer * eoff(2), v0 * inv, v1 * inv, v2 * inv, 1.f);
            t_red = elapsed(0);
            if (layer == 1 && w == 0 && t == 0) st_relaxed2(mlo, 0.f, 0.f);
        }

        if (ffn) {
            const uint32_t a_fst = pin(sb + OFF_FP + (w >> 2) * 256 + ((w & 1) * 8 + g) * 16 + ((w >> 1) & 1) * 8, lane);
            const bool fst = t == (w >> 1);
            const uint32_t a_frd = pin(sb + OFF_FP + (lane & 15) * 16, lane);
            const uint32_t a_w2 = sb + OFF_W2 + w * 2048 + ((mi >> 1) * 8 + li) * 128 + (((mi & 1) ^ li) << 4);
            if (layer == 0) {
                while (todo) { if (gtime() - g0 >= due) issue(16 | 32); keep(); }
            }
            const uint32_t a_w13 = sb + OFF_W13 + (w >> 2) * 16384 + (mi & 1) * 8192 + (((w >> 1) & 1) * 128 + (mi >> 1) * 8 + li) * 32 + (((w & 1) ^ (li >> 2)) << 4);
            auto stage_w13 = [&]() {
#pragma unroll
                for (int j = 0; j < 8; j++) ldsm4t(S[j], a_w13 + j * 16 * 32);
                if (layer == 0) {
                    float c0[4], c1[4];
                    zero4(c0); zero4(c1);
#pragma unroll
                    for (int j = 0; j < 4; j++) { mma(c0, S[2 * j], ONES, ONES); mma(c1, S[2 * j + 1], ONES, ONES); }
                    if (t == 0) asm volatile("st.shared.v2.f32 [%0], {%1,%2};" ::"r"(a_fst + (OFF_FC - OFF_FP)), "f"(c0[0] + c1[0]), "f"(c0[2] + c1[2]) : "memory");
                }
            };
            if (layer == 0) {
                const uint32_t bw1 = sb + OFF_BAR + (w >> 2) * 2 * BS + B_F;
                bool staged = false, more;
                int n = SPIN_LIMIT;
                while (gtime() - g0 < P1NS) {
                    keep();
                    if (!staged && mbar_test(bw1) && mbar_test(bw1 + BS)) { stage_w13(); staged = true; }
                }
                do {
                    const float4 v = ld_relaxed4(accp), v2 = ld_relaxed4(accp + 256);
                    keep();
                    if (!staged && mbar_test(bw1) && mbar_test(bw1 + BS)) { stage_w13(); staged = true; }
                    --n;
                    more = __any_sync(0xffffffffu, v.w + v2.w != (float)(NCTA + 2) && n > 0);
                    put_x(v.x + v2.x, v.y + v2.y, v.z + v2.z);
                } while (more);
                if (!staged) { gated_wait(bw1, 0, true); gated_wait(bw1 + BS, 0, true); stage_w13(); }
                commit_x();
            } else {
                stage_w13();
#pragma unroll
                for (int j = 0; j < 4; j++) ldsm4t(S[8 + j], a_w2 ^ (j << 5));
                exchange_wait(accp + eoff(2), (float)NCTA, PD3);
            }
            {
                uint4 u0 = lds128(a_row + OFF_XS), u1 = lds128(a_row + OFF_XS + 16);
                if (layer == 0) {
                    float4 p0 = lds128f(a_frd + (OFF_FC - OFF_FP)), p1 = lds128f(a_frd + (OFF_FC - OFF_FP) + 256);
                    cs_g = (p0.x + p0.z) + (p1.x + p1.z);
                    cs_u = (p0.y + p0.w) + (p1.y + p1.w);
                }
                {
                    const uint32_t z0 = own ? p01 : 0u, z1 = t < 2 ? p2 : 0u;
                    float c[4];
                    zero4(c);
                    mma_ab(c, z0, ONES, z1, ONES, z0, z1);
                    float s_ = c[2] + c[3], q_ = (g & 1) ? c[1] : c[0];
                    q_ += __shfl_xor_sync(0xffffffffu, q_, 4);
                    s_ += __shfl_xor_sync(0xffffffffu, s_, 1);
                    q_ += __shfl_xor_sync(0xffffffffu, q_, 9);
                    s_ += __shfl_xor_sync(0xffffffffu, s_, 2);
                    q_ += __shfl_xor_sync(0xffffffffu, q_, 18);
                    if (lane == 0) { sts32f(a_qo + OFF_SQ, s_); sts32f(a_qo + OFF_SQ + 32, q_); }
                }
                float acc[4][4];
                zero4(acc[0]); zero4(acc[1]); zero4(acc[2]); zero4(acc[3]);
                mma(acc[0], S[0], u0.x, u0.y); mma(acc[1], S[4], u0.x, u0.y); mma(acc[2], S[2], u1.x, u1.y); mma(acc[3], S[6], u1.x, u1.y);
                mma(acc[0], S[1], u0.z, u0.w); mma(acc[1], S[5], u0.z, u0.w); mma(acc[2], S[3], u1.z, u1.w); mma(acc[3], S[7], u1.z, u1.w);
                if (fst) asm volatile("st.shared.v2.f32 [%0], {%1,%2};" ::"r"(a_fst), "f"((acc[0][0] + acc[2][0]) + (acc[1][1] + acc[3][1])),
                                      "f"((acc[0][2] + acc[2][2]) + (acc[1][3] + acc[3][3])) : "memory");
            }
            cta_sync();
            {
                const float4 s0 = lds128f(a_sb + OFF_SQ), s1 = lds128f(a_sb + OFF_SQ + 16), q0 = lds128f(a_sb + OFF_SQ + 32), q1 = lds128f(a_sb + OFF_SQ + 48);
                float4 p0 = lds128f(a_frd), p1 = lds128f(a_frd + 256);
                const float mean2 = (((s0.x + s0.y) + (s0.z + s0.w)) + ((s1.x + s1.y) + (s1.z + s1.w))) * (1.f / 512.f);
                const float ssq = ((q0.x + q0.y) + (q0.z + q0.w)) + ((q1.x + q1.y) + (q1.z + q1.w));
                const float rstd2 = rsq(fmaxf(fmaf(-mean2, mean2, fmaf(ssq, 1.f / 512.f, 1e-5f)), 1e-5f));
                if (layer == 0) {
                    mbar_wait(sb + OFF_BAR + (4 + (w >> 1)) * BS + B_F, 0);
#pragma unroll
                    for (int j = 0; j < 4; j++) ldsm4t(S[8 + j], a_w2 ^ (j << 5));
                }
                float gate = rstd2 * (fmaf(-mean2, cs_g, p0.x + p0.z) + (p1.x + p1.z));
                float up = rstd2 * (fmaf(-mean2, cs_u, p0.y + p0.w) + (p1.y + p1.w));
                float hv = gate * up * rcp(1.f + ex2(-1.4426950408889634f * gate));
                float h0 = __shfl_sync(0xffffffffu, hv, 2 * t), h1 = __shfl_sync(0xffffffffu, hv, 2 * t + 1);
                float h2 = __shfl_sync(0xffffffffu, hv, 2 * t + 8), h3 = __shfl_sync(0xffffffffu, hv, 2 * t + 9);
                const uint32_t b0 = pack_bf16(h0, h1), b1 = pack_bf16(h2, h3);
                float y[4][4];
#pragma unroll
                for (int j = 0; j < 4; j++) {
                    zero4(y[j]);
                    mma(y[j], S[8 + j], b0, b1);
                }
                float v0 = (t == 0) ? y[0][0] : (t == 1) ? y[1][2] : y[3][0];
                float v1 = (t == 0) ? y[0][2] : (t == 1) ? y[2][0] : y[3][2];
                float v2 = (t == 0) ? y[1][0] : (t == 1) ? y[2][2] : 0.f;
                if (layer == 0) {
                    if (own) red4(accw + eoff(1), v0, v1, v2, 1.f);
                    t_red = elapsed(0);
                } else if (own) {
                    float4 old = atom4(accp + eoff(3) + (g & 1) * 208, v0, v1, v2, 1.f);
                    if (b < 2) st_relaxed4(accw + eoff(0), 0.f, 0.f, 0.f, 0.f);
                    if (old.w == (float)(NFFN - 1)) {
                        const int c = 64 * w + 24 * t + g;
                        out[c] = __float2bfloat16(xo[0] + (old.x + v0));
                        out[c + 8] = __float2bfloat16(xo[1] + (old.y + v1));
                        if (t < 2) out[c + 16] = __float2bfloat16(xo[2] + (old.z + v2));
                    }
                }
            }
        }
    }
}

typedef CUresult (*EncodeFn)(CUtensorMap*, CUtensorMapDataType, cuuint32_t, void*, const cuuint64_t*, const cuuint64_t*,
                             const cuuint32_t*, const cuuint32_t*, CUtensorMapInterleave, CUtensorMapSwizzle,
                             CUtensorMapL2promotion, CUtensorMapFloatOOBfill);

void make_map(EncodeFn enc, CUtensorMap* m, const void* p, uint64_t cols, uint64_t rows, uint32_t bc, uint32_t br) {
    cuuint64_t gd[2] = {cols, rows};
    cuuint64_t gs[1] = {cols * 2};
    cuuint32_t bd[2] = {bc, br};
    cuuint32_t es[2] = {1, 1};
    enc(m, CU_TENSOR_MAP_DATA_TYPE_BFLOAT16, 2, const_cast<void*>(p), gd, gs, bd, es, CU_TENSOR_MAP_INTERLEAVE_NONE,
        bc == 64 ? CU_TENSOR_MAP_SWIZZLE_128B : CU_TENSOR_MAP_SWIZZLE_32B, CU_TENSOR_MAP_L2_PROMOTION_NONE,
        CU_TENSOR_MAP_FLOAT_OOB_FILL_NONE);
}

}

extern "C" void kernel_launch(void* const* d_in, const int* in_sizes, int n_in, void* d_out, int out_size) {
    (void)in_sizes; (void)n_in; (void)out_size;
    static EncodeFn enc = nullptr;
    static unsigned char* acc = nullptr;
    static MlRow* ml = nullptr;
    if (!enc) {
        void* p = nullptr;
        cudaGetSymbolAddress(&p, g_acc_raw);
        acc = reinterpret_cast<unsigned char*>((reinterpret_cast<uintptr_t>(p) + 32767) & ~(uintptr_t)32767);
        cudaGetSymbolAddress(&p, g_ml_buf);
        ml = reinterpret_cast<MlRow*>(p);
        cudaDriverEntryPointQueryResult qr;
        void* fn = nullptr;
        cudaGetDriverEntryPoint("cuTensorMapEncodeTiled", &fn, cudaEnableDefault, &qr);
        enc = (EncodeFn)fn;
        cudaFuncSetAttribute(fused_kernel, cudaFuncAttributeMaxDynamicSharedMemorySize, (int)SMEM_BYTES);
    }
    Maps mp;
    make_map(enc, &mp.wq, d_in[3], 4096, 512, 64, 256);
    make_map(enc, &mp.k, d_in[1], 128, 32 * 4096, 64, 64);
    make_map(enc, &mp.v, d_in[2], 128, 32 * 4096, 64, 64);
    make_map(enc, &mp.wo, d_in[4], 512, 4096, 64, 64);
    make_map(enc, &mp.w1, d_in[6], 1376, 512, 16, 256);
    make_map(enc, &mp.w3, d_in[7], 1376, 512, 16, 256);
    make_map(enc, &mp.w2, d_in[8], 512, 1376, 64, 16);
    fused_kernel<<<NCTA, NTHR, SMEM_BYTES>>>((const __nv_bfloat16*)d_in[0], (__nv_bfloat16*)d_out, acc, ml, mp);
}
```
